```python
import torch

def _softmax(x, axis=-1):
    return torch.softmax(x, dim=axis)
def _gelu(x):
    return torch.nn.functional.gelu(x, approximate="tanh")
def _silu(x):
    return torch.nn.functional.silu(x)
def _sigmoid(x):
    return torch.sigmoid(x)
def _layernorm(x, axis=-1, eps=1e-5):
    m = x.mean(dim=axis, keepdim=True)
    v = x.var(dim=axis, keepdim=True, unbiased=False)
    return (x - m) / torch.sqrt(v + eps)
def _scatter_add(tgt, idx, src, axis=0):
    return tgt.clone().index_add_(axis, idx, src)
def _segment_sum(src, seg, n):
    out = torch.zeros((n,) + src.shape[1:], dtype=src.dtype)
    return out.index_add_(0, seg, src)
def _pad(x, pw):
    flat = tuple(v for pair in reversed(pw) for v in pair)
    return torch.nn.functional.pad(x, flat)

kernel_name = 'gated_mix__ssm_conv_s5__swiglu_ffn__prompt'

def setup_inputs():

    _w = (lambda a: (lambda t: t.to(torch.bfloat16) if t.is_floating_point() else t)(torch.as_tensor(a)))
    def _A_setup():
        B, S, D = 1, 2048, 640
        P = D
        Lambda_re = -0.5 * (lambda _x: torch.exp(torch.as_tensor(_x)))((lambda *s: torch.randn(*s, dtype=torch.bfloat16) * 0.2)(P))
        Lambda_im = (lambda *s: torch.randn(*s, dtype=torch.bfloat16) * 0.4)(P) * 1.0
        B_re = (lambda *s: torch.randn(*s, dtype=torch.bfloat16) * 0.2)(P, D) * (D ** -0.5)
        B_im = (lambda *s: torch.randn(*s, dtype=torch.bfloat16) * 0.2)(P, D) * (D ** -0.5)
        C_re = (lambda *s: torch.randn(*s, dtype=torch.bfloat16) * 0.2)(D, P) * (P ** -0.5)
        C_im = (lambda *s: torch.randn(*s, dtype=torch.bfloat16) * 0.2)(D, P) * (P ** -0.5)
        log_dt = (lambda *s: torch.randn(*s, dtype=torch.bfloat16) * 0.2)(P) * 0.3 - 2.0
        Dskip = (lambda *s: torch.randn(*s, dtype=torch.bfloat16) * 0.05)(D)
        return {
            "x": _w((lambda *s: torch.randn(*s, dtype=torch.bfloat16) * 0.05)(B, S, D)),
            "Lambda_re": _w(Lambda_re),
            "Lambda_im": _w(Lambda_im),
            "B_re": _w(B_re),
            "B_im": _w(B_im),
            "C_re": _w(C_re),
            "C_im": _w(C_im),
            "log_dt": _w(log_dt),
            "Dskip": _w(Dskip),
        }
    _A_in = _A_setup()

    def _B_setup():
        B, S, D, F = 1, 2048, 640, 1728
        return {
            "x": _w((lambda *s: torch.randn(*s, dtype=torch.bfloat16) * 0.05)(B, S, D)),
            "w_gate": _w((lambda *s: torch.randn(*s, dtype=torch.bfloat16) * 0.05)(D, F)),
            "w_up": _w((lambda *s: torch.randn(*s, dtype=torch.bfloat16) * 0.05)(D, F)),
            "w_down": _w((lambda *s: torch.randn(*s, dtype=torch.bfloat16) * 0.05)(F, D)),
        }
    _B_in = _B_setup()

    return {
        "A_x": _A_in["x"],
        "A_Lambda_re": _A_in["Lambda_re"],
        "A_Lambda_im": _A_in["Lambda_im"],
        "A_B_re": _A_in["B_re"],
        "A_B_im": _A_in["B_im"],
        "A_C_re": _A_in["C_re"],
        "A_C_im": _A_in["C_im"],
        "A_log_dt": _A_in["log_dt"],
        "A_Dskip": _A_in["Dskip"],
        "B_x": _B_in["x"],
        "B_w_gate": _B_in["w_gate"],
        "B_w_up": _B_in["w_up"],
        "B_w_down": _B_in["w_down"],
        "gate_w": _w((lambda *s: torch.randn(*s, dtype=torch.bfloat16) * 0.05)(640) * 16.0),
    }

def reference(A_x, A_Lambda_re, A_Lambda_im, A_B_re, A_B_im, A_C_re, A_C_im, A_log_dt, A_Dskip, B_x, B_w_gate, B_w_up, B_w_down, gate_w):
    def _A_ref(x, Lambda_re, Lambda_im, B_re, B_im, C_re, C_im, log_dt, Dskip):
        Bsz, L, H = x.shape
        Lam = Lambda_re + 1j * Lambda_im
        Bmat = B_re + 1j * B_im
        Cmat = C_re + 1j * C_im
        dt = torch.exp(log_dt)
        Lam_bar = torch.exp(dt * Lam)
        B_bar = ((Lam_bar - 1.0) / Lam)[:, None] * Bmat
        Bu = torch.einsum("bld,pd->blp", x + 0j, B_bar)
        h = torch.zeros_like(Bu[:, 0, :])
        hs = []
        for t in range(L):
            h = Lam_bar[None, :] * h + Bu[:, t, :]
            hs.append(h)
        hseq = torch.stack(hs, 1)
        y = 2.0 * torch.einsum("blp,dp->bld", hseq, Cmat).real + x * Dskip[None, None, :]
        return y

    def _B_ref(x, w_gate, w_up, w_down):
        g = _silu(x @ w_gate)
        u = x @ w_up
        return (g * u) @ w_down

    x = A_x
    g = _sigmoid((x * gate_w).sum(-1, keepdims=True))
    a = _A_ref(x, A_Lambda_re, A_Lambda_im, A_B_re, A_B_im, A_C_re, A_C_im, A_log_dt, A_Dskip)
    b = _B_ref(x, B_w_gate, B_w_up, B_w_down)
    return g * a + (1 - g) * b
```

```cpp
#include <cuda_runtime.h>
#include <cuda_bf16.h>
#include <cuda.h>
#include <stdint.h>

namespace {

constexpr int DM = 640, FF = 1728;
constexpr int NRB = 16;
constexpr int NFC = 27;
constexpr int NCG = 10;
constexpr int CH = 16384;
constexpr int EXTRA_FC = 22;

constexpr int SM_RES = 0;
constexpr int SM_RING = 10 * CH;
constexpr int ST2 = 40960;
constexpr int SM_BAR = 14 * CH;
constexpr int B_XFULL = SM_BAR;
constexpr int B_FULL1 = B_XFULL + 80;
constexpr int B_EMPTY1 = B_FULL1 + 32;
constexpr int B_FULL2 = B_EMPTY1 + 32;
constexpr int B_EMPTY2 = B_FULL2 + 40;
constexpr int B_G = B_EMPTY2 + 40;
constexpr int B_PEER = B_G + 8;
constexpr int B_RECV = B_PEER + 8;
constexpr int SM_READY = B_RECV + 64;
constexpr int SM_G = SM_BAR + 512;
constexpr int SM_TOTAL = SM_BAR + 1024;
constexpr int SMEM_BYTES = SM_TOTAL + 1024;

struct Params {
  CUtensorMap x, bre, bim, wg, wu, cre, cim, wd, wdw[4];
  const __nv_bfloat16 *xin, *lre, *lim, *logdt, *dskip, *gatew;
  const char *p_cre, *p_cim, *p_wd, *p_wg, *p_wu, *p_bre, *p_bim;
  float* out;
  int use_smid;
};

__device__ __align__(1024) unsigned char g_act[NRB * NFC * CH];
__device__ __align__(1024) unsigned char g_h[NRB * NCG * 2 * CH];
__device__ __align__(16) unsigned long long g_agg[NCG * NRB * 64 * 2];
__device__ unsigned g_flag_act[NRB * 32];
__device__ unsigned g_flag_h[NRB * 32];
__device__ unsigned g_epoch[132];
#define PROF_EV(i)
#define PROF_T0
#define PROF_ACC(v)

__device__ __forceinline__ uint32_t smem_u32(const void* p) { return (uint32_t)__cvta_generic_to_shared(p); }
__device__ __forceinline__ void mbar_init(uint32_t bar, uint32_t cnt) {
  asm volatile("mbarrier.init.shared::cta.b64 [%0], %1;" ::"r"(bar), "r"(cnt) : "memory");
}
__device__ __forceinline__ void mbar_expect_tx(uint32_t bar, uint32_t bytes) {
  asm volatile("mbarrier.arrive.expect_tx.shared::cta.b64 _, [%0], %1;" ::"r"(bar), "r"(bytes) : "memory");
}
__device__ __forceinline__ void mbar_arrive(uint32_t bar) {
  asm volatile("mbarrier.arrive.shared::cta.b64 _, [%0];" ::"r"(bar) : "memory");
}
__device__ __forceinline__ uint32_t mapa(uint32_t addr, uint32_t cta) {
  uint32_t r;
  asm("mapa.shared::cluster.u32 %0, %1, %2;" : "=r"(r) : "r"(addr), "r"(cta));
  return r;
}
__device__ __forceinline__ void mbar_arrive_remote(uint32_t cluster_bar) {
  asm volatile("mbarrier.arrive.release.cluster.shared::cluster.b64 _, [%0];" ::"r"(cluster_bar) : "memory");
}
__device__ __forceinline__ void mbar_wait(uint32_t bar, uint32_t parity) {
  asm volatile("{\n.reg .pred p;\n.reg .u32 c;\nmov.u32 c, 0;\n"
               "W:\nmbarrier.try_wait.parity.shared::cta.b64 p, [%0], %1;\n@p bra D;\n"
               "add.u32 c, c, 1;\nsetp.gt.u32 p, c, 1048576;\n@p trap;\nbra W;\nD:\n}"
               ::"r"(bar), "r"(parity) : "memory");
}
__device__ __forceinline__ void mbar_wait_cluster(uint32_t bar, uint32_t parity) {
  asm volatile("{\n.reg .pred p;\n.reg .u32 c;\nmov.u32 c, 0;\n"
               "W:\nmbarrier.try_wait.parity.acquire.cluster.shared::cta.b64 p, [%0], %1;\n@p bra D;\n"
               "add.u32 c, c, 1;\nsetp.gt.u32 p, c, 1048576;\n@p trap;\nbra W;\nD:\n}"
               ::"r"(bar), "r"(parity) : "memory");
}
__device__ __forceinline__ void trap_if_over(int n, int limit) {
  asm volatile("{\n.reg .pred p;\nsetp.gt.s32 p, %0, %1;\n@p trap;\n}" ::"r"(n), "r"(limit));
}
__device__ __forceinline__ void bulk_load(uint32_t dst, const void* src, uint32_t bytes, uint32_t bar) {
  asm volatile("cp.async.bulk.shared::cluster.global.mbarrier::complete_tx::bytes [%0], [%1], %2, [%3];"
               ::"r"(dst), "l"(src), "r"(bytes), "r"(bar) : "memory");
}
__device__ __forceinline__ void tma2d(uint32_t dst, const CUtensorMap* m, int c0, int c1, uint32_t bar) {
  asm volatile("cp.async.bulk.tensor.2d.shared::cluster.global.mbarrier::complete_tx::bytes [%0], [%1, {%3, %4}], [%2];"
               ::"r"(dst), "l"(m), "r"(bar), "r"(c0), "r"(c1) : "memory");
}
__device__ __forceinline__ void tma5d(uint32_t dst, const CUtensorMap* m, int c0, int c4, uint32_t bar) {
  asm volatile("cp.async.bulk.tensor.5d.shared::cluster.global.mbarrier::complete_tx::bytes [%0], [%1, {%3, %5, %5, %5, %4}], [%2];"
               ::"r"(dst), "l"(m), "r"(bar), "r"(c0), "r"(c4), "r"(0) : "memory");
}
__device__ __forceinline__ void l2_prefetch(const void* p, uint32_t bytes) {
  asm volatile("cp.async.bulk.prefetch.L2.global [%0], %1;" ::"l"(p), "r"(bytes) : "memory");
}
__device__ __forceinline__ void prefetch_map(const CUtensorMap* m) {
  asm volatile("prefetch.tensormap [%0];" ::"l"(m) : "memory");
}
__device__ __forceinline__ void wg_fence() { asm volatile("wgmma.fence.sync.aligned;" ::: "memory"); }
__device__ __forceinline__ void wg_commit() { asm volatile("wgmma.commit_group.sync.aligned;" ::: "memory"); }
template <int N> __device__ __forceinline__ void wg_wait() { asm volatile("wgmma.wait_group.sync.aligned %0;" ::"n"(N) : "memory"); }
template <int R> __device__ __forceinline__ void fence_regs(float (&d)[R]) {
#pragma unroll
  for (int i = 0; i < R; i++) asm volatile("" : "+f"(d[i])::"memory");
}
__device__ __forceinline__ uint64_t desc_k(uint32_t addr) {
  return ((uint64_t)0x40000040u << 32) | (uint64_t)(((addr & 0x3FFFFu) >> 4) | (1u << 16));
}
__device__ __forceinline__ uint64_t desc_mn(uint32_t addr) {
  return ((uint64_t)0x40000040u << 32) | (uint64_t)(((addr & 0x3FFFFu) >> 4) | (512u << 16));
}
__device__ __forceinline__ void bar_sync(int id, int n) { asm volatile("bar.sync %0, %1;" ::"r"(id), "r"(n) : "memory"); }
__device__ __forceinline__ void bar_arrive(int id, int n) { asm volatile("bar.arrive %0, %1;" ::"r"(id), "r"(n) : "memory"); }
__device__ __forceinline__ uint32_t pack_bf16(float lo, float hi) {
  uint32_t r;
  asm("cvt.rn.bf16x2.f32 %0, %1, %2;" : "=r"(r) : "f"(hi), "f"(lo));
  return r;
}
__device__ __forceinline__ float bf_lo(uint32_t v) { return __uint_as_float(v << 16); }
__device__ __forceinline__ float bf_hi(uint32_t v) { return __uint_as_float(v & 0xFFFF0000u); }
__device__ __forceinline__ void st_v4(void* p, uint32_t a, uint32_t b, uint32_t c, uint32_t d) {
  asm volatile("st.global.v4.b32 [%0], {%1, %2, %3, %4};" ::"l"(p), "r"(a), "r"(b), "r"(c), "r"(d) : "memory");
}
struct cplx { float r, i; };
__device__ __forceinline__ cplx cmul(cplx a, cplx b) { return {a.r * b.r - a.i * b.i, a.r * b.i + a.i * b.r}; }
__device__ __forceinline__ cplx cfma(cplx a, cplx b, cplx c) {
  return {fmaf(a.r, b.r, fmaf(-a.i, b.i, c.r)), fmaf(a.r, b.i, fmaf(a.i, b.r, c.i))};
}
__device__ __forceinline__ cplx cshfl_up(cplx a, int d) {
  return {__shfl_up_sync(0xffffffffu, a.r, d, 4), __shfl_up_sync(0xffffffffu, a.i, d, 4)};
}

template <int TA, int TB>
__device__ __forceinline__ void wgmma_n128(float (&d)[64], uint64_t da, uint64_t db, int scale_d) {
  asm volatile("{\n.reg .pred p;\nsetp.ne.b32 p, %66, 0;\n"
    "wgmma.mma_async.sync.aligned.m64n128k16.f32.bf16.bf16 {"
    "%0, %1, %2, %3, %4, %5, %6, %7, %8, %9, %10, %11, %12, %13, %14, %15, "
    "%16, %17, %18, %19, %20, %21, %22, %23, %24, %25, %26, %27, %28, %29, %30, %31, "
    "%32, %33, %34, %35, %36, %37, %38, %39, %40, %41, %42, %43, %44, %45, %46, %47, "
    "%48, %49, %50, %51, %52, %53, %54, %55, %56, %57, %58, %59, %60, %61, %62, %63"
    "}, %64, %65, p, 1, 1, %67, %68;\n}\n"
    : "+f"(d[0]), "+f"(d[1]), "+f"(d[2]), "+f"(d[3]), "+f"(d[4]), "+f"(d[5]), "+f"(d[6]), "+f"(d[7]),
      "+f"(d[8]), "+f"(d[9]), "+f"(d[10]), "+f"(d[11]), "+f"(d[12]), "+f"(d[13]), "+f"(d[14]), "+f"(d[15]),
      "+f"(d[16]), "+f"(d[17]), "+f"(d[18]), "+f"(d[19]), "+f"(d[20]), "+f"(d[21]), "+f"(d[22]), "+f"(d[23]),
      "+f"(d[24]), "+f"(d[25]), "+f"(d[26]), "+f"(d[27]), "+f"(d[28]), "+f"(d[29]), "+f"(d[30]), "+f"(d[31]),
      "+f"(d[32]), "+f"(d[33]), "+f"(d[34]), "+f"(d[35]), "+f"(d[36]), "+f"(d[37]), "+f"(d[38]), "+f"(d[39]),
      "+f"(d[40]), "+f"(d[41]), "+f"(d[42]), "+f"(d[43]), "+f"(d[44]), "+f"(d[45]), "+f"(d[46]), "+f"(d[47]),
      "+f"(d[48]), "+f"(d[49]), "+f"(d[50]), "+f"(d[51]), "+f"(d[52]), "+f"(d[53]), "+f"(d[54]), "+f"(d[55]),
      "+f"(d[56]), "+f"(d[57]), "+f"(d[58]), "+f"(d[59]), "+f"(d[60]), "+f"(d[61]), "+f"(d[62]), "+f"(d[63])
    : "l"(da), "l"(db), "r"(scale_d), "n"(TA), "n"(TB));
}

template <int TA, int TB>
__device__ __forceinline__ void wgmma_n160(float (&d)[80], uint64_t da, uint64_t db, int scale_d) {
  asm volatile("{\n.reg .pred p;\nsetp.ne.b32 p, %82, 0;\n"
    "wgmma.mma_async.sync.aligned.m64n160k16.f32.bf16.bf16 {"
    "%0, %1, %2, %3, %4, %5, %6, %7, %8, %9, %10, %11, %12, %13, %14, %15, "
    "%16, %17, %18, %19, %20, %21, %22, %23, %24, %25, %26, %27, %28, %29, %30, %31, "
    "%32, %33, %34, %35, %36, %37, %38, %39, %40, %41, %42, %43, %44, %45, %46, %47, "
    "%48, %49, %50, %51, %52, %53, %54, %55, %56, %57, %58, %59, %60, %61, %62, %63, "
    "%64, %65, %66, %67, %68, %69, %70, %71, %72, %73, %74, %75, %76, %77, %78, %79"
    "}, %80, %81, p, 1, 1, %83, %84;\n}\n"
    : "+f"(d[0]), "+f"(d[1]), "+f"(d[2]), "+f"(d[3]), "+f"(d[4]), "+f"(d[5]), "+f"(d[6]), "+f"(d[7]),
      "+f"(d[8]), "+f"(d[9]), "+f"(d[10]), "+f"(d[11]), "+f"(d[12]), "+f"(d[13]), "+f"(d[14]), "+f"(d[15]),
      "+f"(d[16]), "+f"(d[17]), "+f"(d[18]), "+f"(d[19]), "+f"(d[20]), "+f"(d[21]), "+f"(d[22]), "+f"(d[23]),
      "+f"(d[24]), "+f"(d[25]), "+f"(d[26]), "+f"(d[27]), "+f"(d[28]), "+f"(d[29]), "+f"(d[30]), "+f"(d[31]),
      "+f"(d[32]), "+f"(d[33]), "+f"(d[34]), "+f"(d[35]), "+f"(d[36]), "+f"(d[37]), "+f"(d[38]), "+f"(d[39]),
      "+f"(d[40]), "+f"(d[41]), "+f"(d[42]), "+f"(d[43]), "+f"(d[44]), "+f"(d[45]), "+f"(d[46]), "+f"(d[47]),
      "+f"(d[48]), "+f"(d[49]), "+f"(d[50]), "+f"(d[51]), "+f"(d[52]), "+f"(d[53]), "+f"(d[54]), "+f"(d[55]),
      "+f"(d[56]), "+f"(d[57]), "+f"(d[58]), "+f"(d[59]), "+f"(d[60]), "+f"(d[61]), "+f"(d[62]), "+f"(d[63]),
      "+f"(d[64]), "+f"(d[65]), "+f"(d[66]), "+f"(d[67]), "+f"(d[68]), "+f"(d[69]), "+f"(d[70]), "+f"(d[71]),
      "+f"(d[72]), "+f"(d[73]), "+f"(d[74]), "+f"(d[75]), "+f"(d[76]), "+f"(d[77]), "+f"(d[78]), "+f"(d[79])
    : "l"(da), "l"(db), "r"(scale_d), "n"(TA), "n"(TB));
}

__device__ __forceinline__ int unit_of(int ftype, int nt, int s, bool& ssm) {
  const int c = ftype * 4 + nt;
  ssm = false;
  if (s == 0) return c;
  if (s == 1) { ssm = true; return c; }
  if (s == 2) {
    if (ftype) return 10 + nt;
    if (nt < 2) return 8 + nt;
    ssm = true;
    return 6 + nt;
  }
  if (s == 3) return 14 + c;
  return 23 + nt;
}

template <bool SSM>
__device__ __forceinline__ void unit_mainloop(float (&acc0)[64], float (&acc1)[64], uint32_t sb, int it0, bool first,
                                              bool swap, bool signal, int wg, int lane) {
#pragma unroll 1
  for (int k = 0; k < 10; k++) {
    const int it = it0 + k, s = it & 3;
    if (first) mbar_wait(sb + B_XFULL + 8 * k, 0);
    mbar_wait(sb + B_FULL1 + 8 * s, (it >> 2) & 1);
    const uint32_t res = sb + SM_RES + k * CH, ring = sb + SM_RING + s * CH;
    const uint32_t xa = swap ? ring : res, wa = swap ? res : ring;
    fence_regs(acc0); fence_regs(acc1);
    wg_fence();
#pragma unroll
    for (int kk = 0; kk < 4; kk++) {
      const int sc = (k | kk) != 0;
      if (SSM) {
        const uint64_t db = desc_k(xa + kk * 32);
        wgmma_n128<0, 0>(acc0, desc_k(wa + kk * 32), db, sc);
        wgmma_n128<0, 0>(acc1, desc_k(wa + 8192 + kk * 32), db, sc);
      } else {
        const uint64_t db = desc_mn(wa + kk * 2048);
        wgmma_n128<0, 1>(acc0, desc_k(xa + kk * 32), db, sc);
        wgmma_n128<0, 1>(acc1, desc_k(xa + 8192 + kk * 32), db, sc);
      }
    }
    wg_commit();
    if (k == 9 && signal) bar_arrive(1 + (wg ^ 1), 256);
    if (k > 0) {
      wg_wait<1>();
      if (lane == 0) mbar_arrive(sb + B_EMPTY1 + 8 * ((it - 1) & 3));
    }
    fence_regs(acc0); fence_regs(acc1);
  }
  wg_wait<0>();
  fence_regs(acc0); fence_regs(acc1);
  if (lane == 0) mbar_arrive(sb + B_EMPTY1 + 8 * ((it0 + 9) & 3));
}

__device__ __forceinline__ void publish_flag(unsigned* flag, unsigned tag, int wg) {
  bar_sync(3 + wg, 128);
  if ((threadIdx.x & 127) == 0) {
    asm volatile("fence.acq_rel.gpu;" ::: "memory");
    asm volatile("st.relaxed.gpu.global.u32 [%0], %1;" ::"l"(flag), "r"(tag) : "memory");
  }
}

__device__ __forceinline__ void ffn_half(const float (&a)[64], unsigned char* tile, int mh, int w, int lane) {
  const int q = lane & 3, r = lane >> 2;
#pragma unroll
  for (int hi = 0; hi < 2; hi++) {
    const int m7 = 4 * (w & 1) + 2 * hi + (r & 1);
    const int m = (2 * mh + (w >> 1)) * 32 + (r >> 1) * 8 + m7;
    uint32_t p[8];
#pragma unroll
    for (int j = 0; j < 8; j++) {
      float v[2];
#pragma unroll
      for (int e = 0; e < 2; e++) {
        const float g = a[4 * j + 2 * hi + e], u = a[32 + 4 * j + 2 * hi + e];
        v[e] = __fdividef(g * u, 1.0f + __expf(-g));
      }
      p[j] = pack_bf16(v[0], v[1]);
    }
    unsigned char* row = tile + m * 128;
    st_v4(row + ((q ^ m7) << 4), p[0], p[1], p[2], p[3]);
    st_v4(row + (((4 + q) ^ m7) << 4), p[4], p[5], p[6], p[7]);
  }
}

struct SsmCoef { cplx lam, c, l32, mu; };
__device__ __forceinline__ SsmCoef ssm_coef(const Params& P, int p) {
  const float lr = __bfloat162float(P.lre[p]), li = __bfloat162float(P.lim[p]);
  const float dt = __bfloat162float(__float2bfloat16_rn(expf(__bfloat162float(P.logdt[p]))));
  float sn, cs;
  sincosf(dt * li, &sn, &cs);
  const float ex = expf(dt * lr);
  SsmCoef o;
  o.lam = {ex * cs, ex * sn};
  const float nr = o.lam.r - 1.0f, ni = o.lam.i, den = 1.0f / (lr * lr + li * li);
  o.c = {(nr * lr + ni * li) * den, (ni * lr - nr * li) * den};
  cplx t = o.lam;
#pragma unroll
  for (int i = 0; i < 5; i++) t = cmul(t, t);
  o.l32 = t;
  t = cmul(t, t);
  o.mu = cmul(t, t);
  return o;
}

__device__ __forceinline__ void ssm_epilogue(const float (&vr)[64], const float (&vi)[64], const SsmCoef (&co)[2], int rb,
                                             int cg, unsigned tag, int w, int lane) {
  const int q = lane & 3, r = lane >> 2;
  cplx s[2], init[2];
#pragma unroll
  for (int hi = 0; hi < 2; hi++) s[hi] = {vr[2 * hi], vi[2 * hi]};
#pragma unroll
  for (int t = 1; t < 32; t++)
#pragma unroll
    for (int hi = 0; hi < 2; hi++) {
      const int i = 4 * (t >> 1) + 2 * hi + (t & 1);
      s[hi] = cfma(co[hi].lam, s[hi], cplx{vr[i], vi[i]});
    }
  unsigned long long* agg = g_agg + (size_t)(cg * NRB) * 128;
#pragma unroll
  for (int hi = 0; hi < 2; hi++) {
    const cplx l64 = cmul(co[hi].l32, co[hi].l32);
    cplx y = cshfl_up(s[hi], 1);
    if (q >= 1) s[hi] = cfma(co[hi].l32, y, s[hi]);
    y = cshfl_up(s[hi], 2);
    if (q >= 2) s[hi] = cfma(l64, y, s[hi]);
    if (q == 3 && rb < NRB - 1) {
      const unsigned long long a = ((unsigned long long)tag << 32) | __float_as_uint(s[hi].r);
      const unsigned long long b = ((unsigned long long)tag << 32) | __float_as_uint(s[hi].i);
      asm volatile("st.relaxed.gpu.global.v2.b64 [%0], {%1, %2};" ::"l"(agg + (rb * 64 + 16 * w + r + 8 * hi) * 2), "l"(a), "l"(b) : "memory");
    }
    y = cshfl_up(s[hi], 1);
    init[hi] = q >= 1 ? y : cplx{0.f, 0.f};
  }
  if (rb > 0) {
    cplx e[2][4];
    int spin = 0;
    while (true) {
      bool ok = true;
#pragma unroll
      for (int m = 0; m < 4; m++) {
        const int j = rb - 1 - q - 4 * m;
#pragma unroll
        for (int hi = 0; hi < 2; hi++) {
          unsigned long long a = (unsigned long long)tag << 32, b = a;
          if (j >= 0)
            asm volatile("ld.relaxed.gpu.global.v2.b64 {%0, %1}, [%2];" : "=l"(a), "=l"(b) : "l"(agg + (j * 64 + 16 * w + r + 8 * hi) * 2) : "memory");
          ok = ok && (unsigned)(a >> 32) == tag && (unsigned)(b >> 32) == tag;
          e[hi][m] = {__uint_as_float((unsigned)a), __uint_as_float((unsigned)b)};
        }
      }
      if (__all_sync(0xffffffffu, ok)) break;
      trap_if_over(++spin, 1 << 21);
    }
#pragma unroll
    for (int hi = 0; hi < 2; hi++) {
      const cplx mu = co[hi].mu, mu2 = cmul(mu, mu), mu4 = cmul(mu2, mu2);
      cplx a = cfma(mu4, e[hi][3], e[hi][2]);
      a = cfma(mu4, a, e[hi][1]);
      a = cfma(mu4, a, e[hi][0]);
      if (q & 1) a = cmul(a, mu);
      if (q & 2) a = cmul(a, mu2);
      a.r += __shfl_xor_sync(0xffffffffu, a.r, 1); a.i += __shfl_xor_sync(0xffffffffu, a.i, 1);
      a.r += __shfl_xor_sync(0xffffffffu, a.r, 2); a.i += __shfl_xor_sync(0xffffffffu, a.i, 2);
      if (q & 1) a = cmul(a, co[hi].l32);
      if (q & 2) a = cmul(a, cmul(co[hi].l32, co[hi].l32));
      init[hi].r += a.r; init[hi].i += a.i;
    }
  }
  unsigned char* tile = g_h + (size_t)((rb * NCG + cg) * 2) * CH;
#pragma unroll
  for (int i8 = 0; i8 < 4; i8++) {
    uint32_t pr[2][4], pi[2][4];
#pragma unroll
    for (int jj = 0; jj < 4; jj++) {
#pragma unroll
      for (int hi = 0; hi < 2; hi++) {
        float hr[2], hn[2];
#pragma unroll
        for (int e = 0; e < 2; e++) {
          const int i = 4 * (4 * i8 + jj) + 2 * hi + e;
          init[hi] = cfma(co[hi].lam, init[hi], cplx{vr[i], vi[i]});
          hr[e] = co[hi].c.r * init[hi].r - co[hi].c.i * init[hi].i;
          hn[e] = -co[hi].c.r * init[hi].i - co[hi].c.i * init[hi].r;
        }
        pr[hi][jj] = pack_bf16(hr[0], hr[1]);
        pi[hi][jj] = pack_bf16(hn[0], hn[1]);
      }
    }
#pragma unroll
    for (int hi = 0; hi < 2; hi++) {
      unsigned char* a = tile + (i8 >> 1) * 8192 + (16 * w + 8 * hi + r) * 128 + ((((i8 & 1) * 4 + q) ^ r) << 4);
      st_v4(a, pr[hi][0], pr[hi][1], pr[hi][2], pr[hi][3]);
      st_v4(a + CH, pi[hi][0], pi[hi][1], pi[hi][2], pi[hi][3]);
    }
  }
}

template <bool F>
__device__ __forceinline__ void phase2(const Params& P, uint32_t sb, int rb, int nt, int wg, int w, int lane
) {
  constexpr int NK = F ? NFC : 2 * NCG;
  const int q = lane & 3, r = lane >> 2, warp = wg * 4 + w;
  const int m0 = 64 * wg + 16 * w + r;
  const int mk = m0 + (F ? 8 : 0), ms = m0 + (F ? 0 : 8);
  const int tk = 32 * ((mk >> 3) & 3) + 8 * (mk >> 5) + (mk & 7);
  const int ts = 32 * ((ms >> 3) & 3) + 8 * (ms >> 5) + (ms & 7);
  const int rot = (F && (nt & 1)) ? 2 : 0;
  uint32_t xd[20];
  {
    const __nv_bfloat16* xr = P.xin + (size_t)(rb * 128 + tk) * DM + 160 * nt + 2 * q;
    const __nv_bfloat16* dr = P.dskip + 160 * nt + 2 * q;
#pragma unroll
    for (int j = 0; j < 20; j++) {
      int dj = j + 2 * rot;
      if (dj >= 20) dj -= 20;
      const __nv_bfloat162 a = __ldg((const __nv_bfloat162*)(xr + 8 * dj)), b = __ldg((const __nv_bfloat162*)(dr + 8 * dj));
      const __nv_bfloat162 c = __hmul2(a, b);
      xd[j] = *(const uint32_t*)&c;
    }
  }
  if (lane == 0) mbar_expect_tx(sb + B_RECV + 8 * warp, 5120);
  asm volatile("barrier.cluster.wait.acquire.aligned;" ::: "memory");
  const uint32_t peer = F ? 0 : 1;
  float acc[80];
  int s = 0, ph = 0, ps = 0;
  PROF_EV(32 + wg * 8 + 0);
#pragma unroll 1
  for (int k = 0; k < NK; k++) {
    { PROF_T0; mbar_wait(sb + B_FULL2 + 8 * s, ph); PROF_ACC(pw); }
    const uint32_t a = sb + s * ST2 + wg * 8192, b = sb + s * ST2 + CH;
    fence_regs(acc);
    wg_fence();
#pragma unroll
    for (int kk = 0; kk < 4; kk++) {
      const int sc = (k | kk) != 0;
      if (F) wgmma_n160<0, 1>(acc, desc_k(a + kk * 32), desc_mn(b + kk * 2048), sc);
      else   wgmma_n160<1, 0>(acc, desc_mn(a + kk * 2048), desc_k(b + kk * 32), sc);
    }
    wg_commit();
    if (k > 0) {
      wg_wait<1>();
      if (lane == 0) {
        if (k - 1 < NK - 5) mbar_arrive(sb + B_EMPTY2 + 8 * ps);
        else if (k - 1 == NK - 5) mbar_arrive_remote(mapa(sb + B_PEER, peer));
      }
    }
    fence_regs(acc);
    ps = s;
    if (++s == 5) { s = 0; ph ^= 1; }
  }
  mbar_wait(sb + B_G, 0);
  float gk, gs;
  asm volatile("ld.shared.f32 %0, [%1];" : "=f"(gk) : "r"(sb + SM_G + 4 * tk));
  asm volatile("ld.shared.f32 %0, [%1];" : "=f"(gs) : "r"(sb + SM_G + 4 * ts));
  const float sk = F ? 1.0f - gk : 2.0f * gk, ss = F ? 1.0f - gs : 2.0f * gs;
  mbar_wait_cluster(sb + B_PEER, 0);
  wg_wait<0>();
  fence_regs(acc);
  PROF_EV(32 + wg * 8 + 1);
  constexpr int RSLOT_PEER = F ? (2 * NCG) % 5 : NFC % 5, RSLOT = NK % 5;
  const uint32_t rdst = mapa(sb + RSLOT_PEER * ST2 + warp * 5120 + lane * 16, peer);
  const uint32_t rbar = mapa(sb + B_RECV + 8 * warp, peer);
  constexpr int OS = F ? 0 : 2, OK = F ? 2 : 0;
#pragma unroll
  for (int i = 0; i < 10; i++) {
    int c = i + rot;
    if (c >= 10) c -= 10;
    asm volatile("st.async.weak.shared::cluster.mbarrier::complete_tx::bytes.v4.f32 [%0], {%1, %2, %3, %4}, [%5];"
                 ::"r"(rdst + c * 512), "f"(acc[8 * i + OS] * ss), "f"(acc[8 * i + OS + 1] * ss),
                   "f"(acc[8 * i + 4 + OS] * ss), "f"(acc[8 * i + 4 + OS + 1] * ss), "r"(rbar) : "memory");
  }
  float* orow = P.out + (size_t)(rb * 128 + tk) * DM + 160 * nt + 2 * q;
  mbar_wait_cluster(sb + B_RECV + 8 * warp, 0);
  PROF_EV(32 + wg * 8 + 2);
#pragma unroll
  for (int i = 0; i < 10; i++) {
    int c = i + rot;
    if (c >= 10) c -= 10;
    float4 v;
    asm volatile("ld.shared.v4.f32 {%0, %1, %2, %3}, [%4];" : "=f"(v.x), "=f"(v.y), "=f"(v.z), "=f"(v.w)
                 : "r"(sb + RSLOT * ST2 + warp * 5120 + c * 512 + lane * 16));
    float2 o0, o1;
    o0.x = fmaf(acc[8 * i + OK], sk, fmaf(gk, bf_lo(xd[2 * i]), v.x));
    o0.y = fmaf(acc[8 * i + OK + 1], sk, fmaf(gk, bf_hi(xd[2 * i]), v.y));
    o1.x = fmaf(acc[8 * i + 4 + OK], sk, fmaf(gk, bf_lo(xd[2 * i + 1]), v.z));
    o1.y = fmaf(acc[8 * i + 4 + OK + 1], sk, fmaf(gk, bf_hi(xd[2 * i + 1]), v.w));
    *(float2*)(orow + 16 * c) = o0;
    *(float2*)(orow + 16 * c + 8) = o1;
  }
  PROF_EV(32 + wg * 8 + 3);
}

__global__ void __launch_bounds__(384, 1) __cluster_dims__(2, 1, 1) fused_kernel(const __grid_constant__ Params P) {
  extern __shared__ __align__(1024) unsigned char smem_raw[];
  const uint32_t sb = (smem_u32(smem_raw) + 1023) & ~1023u;
  const int warp = threadIdx.x >> 5, lane = threadIdx.x & 31;
  uint32_t ftype, smid;
  asm("mov.u32 %0, %%cluster_ctarank;" : "=r"(ftype));
  asm("mov.u32 %0, %%smid;" : "=r"(smid));
  const int tp = P.use_smid ? (int)(smid >> 1) : (int)(blockIdx.x >> 1);
  int gpc, idx;
  bool extra = false;
  if (tp < 32) { gpc = tp & 7; idx = tp >> 3; }
  else if (tp < 60) { gpc = 1 + (tp - 32) % 7; idx = 4 + (tp - 32) / 7; }
  else if (tp < 62) { gpc = 0; idx = tp - 60; extra = true; }
  else { gpc = 0; idx = tp - 58; }
  const int rb = extra ? (idx * 2 + ftype) * 4 : 2 * gpc + (idx >> 2);
  const int nt = idx & 3;
  const int role = tp * 2 + ftype;
  const int nslots = (extra || ftype) ? 4 : 5;

  if (threadIdx.x == 256) {
    for (int i = 0; i < 10; i++) mbar_init(sb + B_XFULL + 8 * i, 1);
    for (int i = 0; i < 4; i++) { mbar_init(sb + B_FULL1 + 8 * i, 1); mbar_init(sb + B_EMPTY1 + 8 * i, 4); }
    for (int i = 0; i < 5; i++) { mbar_init(sb + B_FULL2 + 8 * i, 1); mbar_init(sb + B_EMPTY2 + 8 * i, 8); }
    mbar_init(sb + B_G, 64);
    mbar_init(sb + B_PEER, 8);
    for (int i = 0; i < 8; i++) mbar_init(sb + B_RECV + 8 * i, 1);
    asm volatile("st.shared.u32 [%0], %1;" ::"r"(sb + SM_READY), "r"(0) : "memory");
    asm volatile("fence.mbarrier_init.release.cluster;" ::: "memory");
    asm volatile("fence.proxy.async.shared::cta;" ::: "memory");
    const int fc0 = extra ? EXTRA_FC : ftype * 4 + nt;
    for (int k = 0; k < 10; k++) {
      const uint32_t res = sb + SM_RES + k * CH, ring = sb + SM_RING + k * CH;
      const uint32_t bx = sb + B_XFULL + 8 * k, bf = sb + B_FULL1 + 8 * k;
      mbar_expect_tx(bx, CH);
      if (k < 4) mbar_expect_tx(bf, CH);
      if (!extra) {
        tma5d(res, &P.x, 64 * k, rb, bx);
        if (k < 4) { tma2d(ring, &P.wg, 64 * fc0, 64 * k, bf); tma2d(ring + 8192, &P.wu, 64 * fc0, 64 * k, bf); }
      } else {
        tma2d(res, &P.wg, 64 * fc0, 64 * k, bx); tma2d(res + 8192, &P.wu, 64 * fc0, 64 * k, bx);
        if (k < 4) tma5d(ring, &P.x, 64 * k, rb, bf);
      }
    }
  }
  unsigned tag;
  asm volatile("ld.relaxed.gpu.global.u32 %0, [%1];" : "=r"(tag) : "l"(g_epoch + role) : "memory");
  __syncthreads();
  asm volatile("barrier.cluster.arrive.release.aligned;" ::: "memory");

  if (warp >= 8) {
    asm volatile("setmaxnreg.dec.sync.aligned.u32 40;");
    if (warp == 8) {
      if (lane == 0) {
        const int n1 = nslots * 10;
        int slot = 0, k = 4;
        bool ssm = false;
        int id = extra ? 0 : unit_of(ftype, nt, 0, ssm);
        for (int it = 4; it < n1; it++) {
          if (k == 10) { k = 0; slot++; if (!extra) id = unit_of(ftype, nt, slot, ssm); }
          const int s = it & 3;
          const uint32_t ring = sb + SM_RING + s * CH, bf = sb + B_FULL1 + 8 * s;
          { PROF_T0; mbar_wait(sb + B_EMPTY1 + 8 * s, ((it >> 2) & 1) ^ 1); PROF_ACC(pw1); }
          mbar_expect_tx(bf, CH);
          if (extra) tma5d(ring, &P.x, 64 * k, rb + slot, bf);
          else if (ssm) { tma2d(ring, &P.bre, 64 * k, 64 * id, bf); tma2d(ring + 8192, &P.bim, 64 * k, 64 * id, bf); }
          else { tma2d(ring, &P.wg, 64 * id, 64 * k, bf); tma2d(ring + 8192, &P.wu, 64 * id, 64 * k, bf); }
          k++;
        }
        if (!extra) {
          const int nk = ftype ? NFC : 2 * NCG;
          const int d0 = 160 * nt + ((nt & 1) ? 32 : 0);
          mbar_wait(sb + B_G, 0);
          int s = 0, ph = 1;
          uint32_t ready = 0;
          for (int k2 = 0; k2 < nk; k2++) {
            if (k2 == 2) { mbar_wait(sb + B_EMPTY1 + 8 * ((n1 - 4) & 3), ((n1 - 4) >> 2) & 1); mbar_wait(sb + B_EMPTY1 + 8 * ((n1 - 3) & 3), ((n1 - 3) >> 2) & 1); }
            if (k2 == 3) { mbar_wait(sb + B_EMPTY1 + 8 * ((n1 - 2) & 3), ((n1 - 2) >> 2) & 1); mbar_wait(sb + B_EMPTY1 + 8 * ((n1 - 1) & 3), ((n1 - 1) >> 2) & 1); }
            if (k2 >= 5) { PROF_T0; mbar_wait(sb + B_EMPTY2 + 8 * s, ph); PROF_ACC(pw2); }
            const uint32_t st = sb + s * ST2, bf = sb + B_FULL2 + 8 * s;
            const uint32_t need = ftype ? k2 : (k2 >> 1);
            mbar_expect_tx(bf, ftype ? 40960 : 36864);
            if (ftype) {
              tma5d(st + CH, &P.wd, d0, 2 * k2, bf);
              tma5d(st + CH + 8192, &P.wd, d0 + 64, 2 * k2, bf);
              tma5d(st + CH + 16384, &P.wdw[nt], 0, 2 * k2, bf);
            } else {
              tma2d(st + CH, (k2 & 1) ? &P.cim : &P.cre, 64 * (k2 >> 1), 160 * nt, bf);
            }
            if (ready <= need) {
              int spin = 0;
              PROF_T0;
              do {
                asm volatile("ld.acquire.cta.shared.u32 %0, [%1];" : "=r"(ready) : "r"(sb + SM_READY) : "memory");
                trap_if_over(++spin, 1 << 26);
              } while (ready <= need);
              asm volatile("fence.proxy.async.global;" ::: "memory");
              PROF_ACC(pw3);
            }
            bulk_load(st, ftype ? g_act + (size_t)(rb * NFC + k2) * CH : g_h + (size_t)(rb * 2 * NCG + k2) * CH, CH, bf);
            if (++s == 5) { s = 0; ph ^= 1; }
          }
        }
      }
    } else if (warp < 11) {
      if (!extra) {
        const int r0 = (warp - 9) * 64 + lane;
        float a0 = 0.f, a1 = 0.f;
#pragma unroll 1
        for (int k = 0; k < 10; k++) {
          mbar_wait(sb + B_XFULL + 8 * k, 0);
#pragma unroll 2
          for (int c = 0; c < 8; c++) {
            const uint4 gw = __ldg((const uint4*)(P.gatew + 64 * k + 8 * c));
            uint4 u, v;
            const uint32_t ad = sb + SM_RES + k * CH + r0 * 128 + ((c ^ (r0 & 7)) << 4);
            asm volatile("ld.shared.v4.u32 {%0, %1, %2, %3}, [%4];" : "=r"(u.x), "=r"(u.y), "=r"(u.z), "=r"(u.w) : "r"(ad));
            asm volatile("ld.shared.v4.u32 {%0, %1, %2, %3}, [%4];" : "=r"(v.x), "=r"(v.y), "=r"(v.z), "=r"(v.w) : "r"(ad + 32 * 128));
            const uint32_t gg[4] = {gw.x, gw.y, gw.z, gw.w}, uu[4] = {u.x, u.y, u.z, u.w}, vv[4] = {v.x, v.y, v.z, v.w};
#pragma unroll
            for (int i = 0; i < 4; i++) {
              a0 = fmaf(bf_lo(uu[i]), bf_lo(gg[i]), fmaf(bf_hi(uu[i]), bf_hi(gg[i]), a0));
              a1 = fmaf(bf_lo(vv[i]), bf_lo(gg[i]), fmaf(bf_hi(vv[i]), bf_hi(gg[i]), a1));
            }
          }
        }
        const int r1 = r0 + 32;
        const int t0 = 32 * ((r0 >> 1) & 3) + 2 * (r0 >> 3) + (r0 & 1), t1 = 32 * ((r1 >> 1) & 3) + 2 * (r1 >> 3) + (r1 & 1);
        asm volatile("st.shared.f32 [%0], %1;" ::"r"(sb + SM_G + 4 * t0), "f"(1.0f / (1.0f + expf(-a0))) : "memory");
        asm volatile("st.shared.f32 [%0], %1;" ::"r"(sb + SM_G + 4 * t1), "f"(1.0f / (1.0f + expf(-a1))) : "memory");
        mbar_arrive(sb + B_G);
      }
    } else if (!extra) {
      mbar_wait(sb + B_XFULL + 8 * 9, 0);
      if (lane == 0) {
        const int pc = (rb * 4 + nt) * 2 + ftype;
        l2_prefetch(P.p_cre + pc * 6400, 6400);
        l2_prefetch(P.p_cim + pc * 6400, 6400);
        l2_prefetch(P.p_wd + pc * 17280, 17280);
      }
      const int nf = ftype ? NFC : NCG;
      const unsigned* fl = (ftype ? g_flag_act : g_flag_h) + rb * 32 + lane;
      const unsigned want = tag + 1;
      uint32_t last = 0;
      int spin = 0;
      while (last < (uint32_t)nf) {
        unsigned v = want;
        if (lane < nf) asm volatile("ld.acquire.gpu.global.u32 %0, [%1];" : "=r"(v) : "l"(fl) : "memory");
        const unsigned miss = __ballot_sync(0xffffffffu, v != want);
        const uint32_t n = miss ? __ffs(miss) - 1 : 32;
        __syncwarp();
        if (n > last) {
          last = n;
          if (lane == 0) asm volatile("st.release.cta.shared.u32 [%0], %1;" ::"r"(sb + SM_READY), "r"(n) : "memory");
        } else {
          __nanosleep(200);
        }
        trap_if_over(++spin, 1 << 22);
      }
    }
    __syncwarp();
    asm volatile("barrier.cluster.wait.acquire.aligned;" ::: "memory");
  } else {
    asm volatile("setmaxnreg.inc.sync.aligned.u32 232;");
    const int wg = warp >> 2, w = warp & 3;
    const unsigned want = tag + 1;
    bool first = true;
#pragma unroll 1
    for (int slot = (wg + nslots) & 1; slot < nslots; slot += 2) {
      bool ssm = false;
      const int id = extra ? EXTRA_FC : unit_of(ftype, nt, slot, ssm);
      const bool signal = slot + 1 < nslots;
      float acc0[64], acc1[64];
      if (ssm) {
        SsmCoef co[2];
        co[0] = ssm_coef(P, 64 * id + 16 * w + (lane >> 2));
        co[1] = ssm_coef(P, 64 * id + 16 * w + (lane >> 2) + 8);
        bar_sync(1 + wg, 256);
        PROF_EV(slot * 4 + 0);
        unit_mainloop<true>(acc0, acc1, sb, slot * 10, first, false, signal, wg, lane);
        PROF_EV(slot * 4 + 1);
        ssm_epilogue(acc0, acc1, co, rb, id, want, w, lane);
        PROF_EV(slot * 4 + 2);
        publish_flag(g_flag_h + rb * 32 + id, want, wg);
      } else {
        if (slot > 0) bar_sync(1 + wg, 256);
        PROF_EV(slot * 4 + 0);
        unit_mainloop<false>(acc0, acc1, sb, slot * 10, first, extra, signal, wg, lane);
        PROF_EV(slot * 4 + 1);
        const int rbo = extra ? rb + slot : rb;
        unsigned char* tile = g_act + (size_t)(rbo * NFC + id) * CH;
        ffn_half(acc0, tile, 0, w, lane);
        ffn_half(acc1, tile, 1, w, lane);
        PROF_EV(slot * 4 + 2);
        publish_flag(g_flag_act + rbo * 32 + id, want, wg);
      }
      PROF_EV(slot * 4 + 3);
      first = false;
    }
    if (extra) {
      asm volatile("barrier.cluster.wait.acquire.aligned;" ::: "memory");
    } else {
      if (ftype) phase2<true>(P, sb, rb, nt, wg, w, lane);
      else phase2<false>(P, sb, rb, nt, wg, w, lane);
    }
    bar_sync(5, 256);
    if (threadIdx.x == 0) g_epoch[role] = want;
  }
}

typedef CUresult (*EncodeFn)(CUtensorMap*, CUtensorMapDataType, cuuint32_t, void*, const cuuint64_t*, const cuuint64_t*,
                             const cuuint32_t*, const cuuint32_t*, CUtensorMapInterleave, CUtensorMapSwizzle,
                             CUtensorMapL2promotion, CUtensorMapFloatOOBfill);

void encode(EncodeFn fn, CUtensorMap* m, const void* base, int rank, const cuuint64_t* dims, const cuuint64_t* strides,
            const cuuint32_t* box) {
  const cuuint32_t es[5] = {1, 1, 1, 1, 1};
  fn(m, CU_TENSOR_MAP_DATA_TYPE_BFLOAT16, rank, const_cast<void*>(base), dims, strides, box, es,
     CU_TENSOR_MAP_INTERLEAVE_NONE, CU_TENSOR_MAP_SWIZZLE_128B, CU_TENSOR_MAP_L2_PROMOTION_L2_128B,
     CU_TENSOR_MAP_FLOAT_OOB_FILL_NONE);
}

}

extern "C" void kernel_launch(void* const* d_in, const int* in_sizes, int n_in, void* d_out, int out_size) {
  (void)in_sizes; (void)n_in; (void)out_size;
  static EncodeFn enc = nullptr;
  static int sms = 0;
  if (!enc) {
    void* fn = nullptr;
    cudaDriverEntryPointQueryResult qr;
    cudaGetDriverEntryPoint("cuTensorMapEncodeTiled", &fn, cudaEnableDefault, &qr);
    enc = (EncodeFn)fn;
    int dev = 0;
    cudaGetDevice(&dev);
    cudaDeviceGetAttribute(&sms, cudaDevAttrMultiProcessorCount, dev);
    cudaFuncSetAttribute(fused_kernel, cudaFuncAttributeMaxDynamicSharedMemorySize, SMEM_BYTES);
  }
  typedef const __nv_bfloat16* bp;
  Params P;
  const cuuint64_t R = DM * 2;
  {
    const cuuint64_t d[5] = {DM, 2, 4, 16, NRB}, s[4] = {R, 32 * R, 2 * R, 128 * R};
    const cuuint32_t b[5] = {64, 2, 4, 16, 1};
    encode(enc, &P.x, d_in[0], 5, d, s, b);
  }
  {
    const cuuint64_t d[2] = {DM, DM}, s[1] = {R};
    const cuuint32_t b[2] = {64, 64}, bc[2] = {64, 160};
    encode(enc, &P.bre, d_in[3], 2, d, s, b);
    encode(enc, &P.bim, d_in[4], 2, d, s, b);
    encode(enc, &P.cre, d_in[5], 2, d, s, bc);
    encode(enc, &P.cim, d_in[6], 2, d, s, bc);
  }
  {
    const cuuint64_t d[2] = {FF, DM}, s[1] = {FF * 2};
    const cuuint32_t b[2] = {64, 64};
    encode(enc, &P.wg, d_in[10], 2, d, s, b);
    encode(enc, &P.wu, d_in[11], 2, d, s, b);
  }
  {
    cuuint64_t d[5] = {DM, 2, 4, 4, FF / 32};
    const cuuint64_t s[4] = {R, 8 * R, 2 * R, 32 * R};
    const cuuint32_t b[5] = {64, 2, 4, 4, 2};
    encode(enc, &P.wd, d_in[12], 5, d, s, b);
    d[0] = 32;
    for (int nt = 0; nt < 4; nt++) encode(enc, &P.wdw[nt], (bp)d_in[12] + 160 * nt + ((nt & 1) ? 0 : 128), 5, d, s, b);
  }
  P.xin = (bp)d_in[0]; P.lre = (bp)d_in[1]; P.lim = (bp)d_in[2]; P.logdt = (bp)d_in[7]; P.dskip = (bp)d_in[8];
  P.gatew = (bp)d_in[13];
  P.p_bre = (const char*)d_in[3]; P.p_bim = (const char*)d_in[4]; P.p_cre = (const char*)d_in[5]; P.p_cim = (const char*)d_in[6];
  P.p_wg = (const char*)d_in[10]; P.p_wu = (const char*)d_in[11]; P.p_wd = (const char*)d_in[12];
  P.out = (float*)d_out;
  P.use_smid = sms == 132;
  fused_kernel<<<132, 384, SMEM_BYTES, cudaStreamPerThread>>>(P);
}
```

```cpp
#include <cuda_runtime.h>
#include <cuda_bf16.h>
#include <cuda.h>
#include <stdint.h>

namespace {

constexpr int DM = 640, FF = 1728;
constexpr int NRB = 16;
constexpr int NFC = 27;
constexpr int NCG = 10;
constexpr int CH = 16384;
constexpr int EXTRA_FC = 22;

constexpr int SM_RES = 0;
constexpr int SM_RING = 10 * CH;
constexpr int ST2 = 40960;
constexpr int SM_BAR = 14 * CH;
constexpr int B_XFULL = SM_BAR;
constexpr int B_FULL1 = B_XFULL + 80;
constexpr int B_EMPTY1 = B_FULL1 + 32;
constexpr int B_FULL2 = B_EMPTY1 + 32;
constexpr int B_EMPTY2 = B_FULL2 + 40;
constexpr int B_G = B_EMPTY2 + 40;
constexpr int B_PEER = B_G + 8;
constexpr int B_RECV = B_PEER + 8;
constexpr int SM_READY = B_RECV + 64;
constexpr int SM_G = SM_BAR + 512;
constexpr int SM_GW = SM_BAR + 1024;
constexpr int SMEM_BYTES = SM_GW + 1280;

struct Params {
  CUtensorMap x, bre, bim, wg, wu, cre, cim, wd, wdw[4];
  const __nv_bfloat16 *xin, *lre, *lim, *logdt, *dskip, *gatew;
  const char *p_cre, *p_cim, *p_wd, *p_wg, *p_wu, *p_bre, *p_bim;
  float* out;
  int use_smid;
};

__device__ __align__(1024) unsigned char g_act[NRB * NFC * CH];
__device__ __align__(1024) unsigned char g_h[NRB * NCG * 2 * CH];
__device__ __align__(16) unsigned long long g_agg[NCG * NRB * 64 * 2];
__device__ unsigned g_flag_act[NRB * 32];
__device__ unsigned g_flag_h[NRB * 32];
__device__ unsigned g_epoch[132];
#define PROF_EV(i)
#define TR(it, f)
#define PROF_ARGS
#define PROF_T0
#define PROF_ACC(v)

__device__ __forceinline__ uint32_t smem_u32(const void* p) { return (uint32_t)__cvta_generic_to_shared(p); }
__device__ __forceinline__ void mbar_init(uint32_t bar, uint32_t cnt) {
  asm volatile("mbarrier.init.shared::cta.b64 [%0], %1;" ::"r"(bar), "r"(cnt) : "memory");
}
__device__ __forceinline__ void mbar_expect_tx(uint32_t bar, uint32_t bytes) {
  asm volatile("mbarrier.arrive.expect_tx.shared::cta.b64 _, [%0], %1;" ::"r"(bar), "r"(bytes) : "memory");
}
__device__ __forceinline__ void mbar_arrive(uint32_t bar) {
  asm volatile("mbarrier.arrive.shared::cta.b64 _, [%0];" ::"r"(bar) : "memory");
}
__device__ __forceinline__ uint32_t mapa(uint32_t addr, uint32_t cta) {
  uint32_t r;
  asm("mapa.shared::cluster.u32 %0, %1, %2;" : "=r"(r) : "r"(addr), "r"(cta));
  return r;
}
__device__ __forceinline__ void mbar_arrive_remote(uint32_t cluster_bar) {
  asm volatile("mbarrier.arrive.release.cluster.shared::cluster.b64 _, [%0];" ::"r"(cluster_bar) : "memory");
}
__device__ __forceinline__ void mbar_wait(uint32_t bar, uint32_t parity) {
  asm volatile("{\n.reg .pred p;\n.reg .u32 c;\nmov.u32 c, 0;\n"
               "W:\nmbarrier.try_wait.parity.shared::cta.b64 p, [%0], %1;\n@p bra D;\n"
               "add.u32 c, c, 1;\nsetp.gt.u32 p, c, 1048576;\n@p trap;\nbra W;\nD:\n}"
               ::"r"(bar), "r"(parity) : "memory");
}
__device__ __forceinline__ void mbar_wait_cluster(uint32_t bar, uint32_t parity) {
  asm volatile("{\n.reg .pred p;\n.reg .u32 c;\nmov.u32 c, 0;\n"
               "W:\nmbarrier.try_wait.parity.acquire.cluster.shared::cta.b64 p, [%0], %1;\n@p bra D;\n"
               "add.u32 c, c, 1;\nsetp.gt.u32 p, c, 1048576;\n@p trap;\nbra W;\nD:\n}"
               ::"r"(bar), "r"(parity) : "memory");
}
__device__ __forceinline__ void trap_if_over(int n, int limit) {
  asm volatile("{\n.reg .pred p;\nsetp.gt.s32 p, %0, %1;\n@p trap;\n}" ::"r"(n), "r"(limit));
}
__device__ __forceinline__ void bulk_load(uint32_t dst, const void* src, uint32_t bytes, uint32_t bar) {
  asm volatile("cp.async.bulk.shared::cluster.global.mbarrier::complete_tx::bytes [%0], [%1], %2, [%3];"
               ::"r"(dst), "l"(src), "r"(bytes), "r"(bar) : "memory");
}
__device__ __forceinline__ void tma2d(uint32_t dst, const CUtensorMap* m, int c0, int c1, uint32_t bar) {
  asm volatile("cp.async.bulk.tensor.2d.shared::cluster.global.mbarrier::complete_tx::bytes [%0], [%1, {%3, %4}], [%2];"
               ::"r"(dst), "l"(m), "r"(bar), "r"(c0), "r"(c1) : "memory");
}
__device__ __forceinline__ void tma5d(uint32_t dst, const CUtensorMap* m, int c0, int c4, uint32_t bar) {
  asm volatile("cp.async.bulk.tensor.5d.shared::cluster.global.mbarrier::complete_tx::bytes [%0], [%1, {%3, %5, %5, %5, %4}], [%2];"
               ::"r"(dst), "l"(m), "r"(bar), "r"(c0), "r"(c4), "r"(0) : "memory");
}
__device__ __forceinline__ void l2_prefetch(const void* p, uint32_t bytes) {
  asm volatile("cp.async.bulk.prefetch.L2.global [%0], %1;" ::"l"(p), "r"(bytes) : "memory");
}
__device__ __forceinline__ void prefetch_map(const CUtensorMap* m) {
  asm volatile("prefetch.tensormap [%0];" ::"l"(m) : "memory");
}
__device__ __forceinline__ void wg_fence() { asm volatile("wgmma.fence.sync.aligned;" ::: "memory"); }
__device__ __forceinline__ void wg_commit() { asm volatile("wgmma.commit_group.sync.aligned;" ::: "memory"); }
template <int N> __device__ __forceinline__ void wg_wait() { asm volatile("wgmma.wait_group.sync.aligned %0;" ::"n"(N) : "memory"); }
template <int R> __device__ __forceinline__ void fence_regs(float (&d)[R]) {
#pragma unroll
  for (int i = 0; i < R; i++) asm volatile("" : "+f"(d[i])::"memory");
}
__device__ __forceinline__ uint64_t desc_k(uint32_t a16) { return ((uint64_t)0x40000040u << 32) | (uint64_t)(a16 + (1u << 16)); }
__device__ __forceinline__ uint64_t desc_mn(uint32_t a16) { return ((uint64_t)0x40000040u << 32) | (uint64_t)(a16 + (512u << 16)); }
__device__ __forceinline__ void bar_sync(int id, int n) { asm volatile("bar.sync %0, %1;" ::"r"(id), "r"(n) : "memory"); }
__device__ __forceinline__ void bar_arrive(int id, int n) { asm volatile("bar.arrive %0, %1;" ::"r"(id), "r"(n) : "memory"); }
__device__ __forceinline__ uint32_t pack_bf16(float lo, float hi) {
  uint32_t r;
  asm("cvt.rn.bf16x2.f32 %0, %1, %2;" : "=r"(r) : "f"(hi), "f"(lo));
  return r;
}
__device__ __forceinline__ float bf_lo(uint32_t v) { return __uint_as_float(v << 16); }
__device__ __forceinline__ float bf_hi(uint32_t v) { return __uint_as_float(v & 0xFFFF0000u); }
__device__ __forceinline__ void st_v4(void* p, uint32_t a, uint32_t b, uint32_t c, uint32_t d) {
  asm volatile("st.global.v4.b32 [%0], {%1, %2, %3, %4};" ::"l"(p), "r"(a), "r"(b), "r"(c), "r"(d) : "memory");
}
__device__ __forceinline__ float fast_ex2(float x) { float y; asm("ex2.approx.ftz.f32 %0, %1;" : "=f"(y) : "f"(x)); return y; }
__device__ __forceinline__ float fast_rcp(float x) { float y; asm("rcp.approx.ftz.f32 %0, %1;" : "=f"(y) : "f"(x)); return y; }
struct cplx { float r, i; };
__device__ __forceinline__ cplx cmul(cplx a, cplx b) { return {a.r * b.r - a.i * b.i, a.r * b.i + a.i * b.r}; }
__device__ __forceinline__ cplx cfma(cplx a, cplx b, cplx c) {
  return {fmaf(a.r, b.r, fmaf(-a.i, b.i, c.r)), fmaf(a.r, b.i, fmaf(a.i, b.r, c.i))};
}
__device__ __forceinline__ cplx cshfl_up(cplx a, int d) {
  return {__shfl_up_sync(0xffffffffu, a.r, d, 4), __shfl_up_sync(0xffffffffu, a.i, d, 4)};
}

template <int TA, int TB>
__device__ __forceinline__ void wgmma_n128(float (&d)[64], uint64_t da, uint64_t db, int scale_d) {
  asm volatile("{\n.reg .pred p;\nsetp.ne.b32 p, %66, 0;\n"
    "wgmma.mma_async.sync.aligned.m64n128k16.f32.bf16.bf16 {"
    "%0, %1, %2, %3, %4, %5, %6, %7, %8, %9, %10, %11, %12, %13, %14, %15, "
    "%16, %17, %18, %19, %20, %21, %22, %23, %24, %25, %26, %27, %28, %29, %30, %31, "
    "%32, %33, %34, %35, %36, %37, %38, %39, %40, %41, %42, %43, %44, %45, %46, %47, "
    "%48, %49, %50, %51, %52, %53, %54, %55, %56, %57, %58, %59, %60, %61, %62, %63"
    "}, %64, %65, p, 1, 1, %67, %68;\n}\n"
    : "+f"(d[0]), "+f"(d[1]), "+f"(d[2]), "+f"(d[3]), "+f"(d[4]), "+f"(d[5]), "+f"(d[6]), "+f"(d[7]),
      "+f"(d[8]), "+f"(d[9]), "+f"(d[10]), "+f"(d[11]), "+f"(d[12]), "+f"(d[13]), "+f"(d[14]), "+f"(d[15]),
      "+f"(d[16]), "+f"(d[17]), "+f"(d[18]), "+f"(d[19]), "+f"(d[20]), "+f"(d[21]), "+f"(d[22]), "+f"(d[23]),
      "+f"(d[24]), "+f"(d[25]), "+f"(d[26]), "+f"(d[27]), "+f"(d[28]), "+f"(d[29]), "+f"(d[30]), "+f"(d[31]),
      "+f"(d[32]), "+f"(d[33]), "+f"(d[34]), "+f"(d[35]), "+f"(d[36]), "+f"(d[37]), "+f"(d[38]), "+f"(d[39]),
      "+f"(d[40]), "+f"(d[41]), "+f"(d[42]), "+f"(d[43]), "+f"(d[44]), "+f"(d[45]), "+f"(d[46]), "+f"(d[47]),
      "+f"(d[48]), "+f"(d[49]), "+f"(d[50]), "+f"(d[51]), "+f"(d[52]), "+f"(d[53]), "+f"(d[54]), "+f"(d[55]),
      "+f"(d[56]), "+f"(d[57]), "+f"(d[58]), "+f"(d[59]), "+f"(d[60]), "+f"(d[61]), "+f"(d[62]), "+f"(d[63])
    : "l"(da), "l"(db), "r"(scale_d), "n"(TA), "n"(TB));
}

template <int TA, int TB>
__device__ __forceinline__ void wgmma_n160(float (&d)[80], uint64_t da, uint64_t db, int scale_d) {
  asm volatile("{\n.reg .pred p;\nsetp.ne.b32 p, %82, 0;\n"
    "wgmma.mma_async.sync.aligned.m64n160k16.f32.bf16.bf16 {"
    "%0, %1, %2, %3, %4, %5, %6, %7, %8, %9, %10, %11, %12, %13, %14, %15, "
    "%16, %17, %18, %19, %20, %21, %22, %23, %24, %25, %26, %27, %28, %29, %30, %31, "
    "%32, %33, %34, %35, %36, %37, %38, %39, %40, %41, %42, %43, %44, %45, %46, %47, "
    "%48, %49, %50, %51, %52, %53, %54, %55, %56, %57, %58, %59, %60, %61, %62, %63, "
    "%64, %65, %66, %67, %68, %69, %70, %71, %72, %73, %74, %75, %76, %77, %78, %79"
    "}, %80, %81, p, 1, 1, %83, %84;\n}\n"
    : "+f"(d[0]), "+f"(d[1]), "+f"(d[2]), "+f"(d[3]), "+f"(d[4]), "+f"(d[5]), "+f"(d[6]), "+f"(d[7]),
      "+f"(d[8]), "+f"(d[9]), "+f"(d[10]), "+f"(d[11]), "+f"(d[12]), "+f"(d[13]), "+f"(d[14]), "+f"(d[15]),
      "+f"(d[16]), "+f"(d[17]), "+f"(d[18]), "+f"(d[19]), "+f"(d[20]), "+f"(d[21]), "+f"(d[22]), "+f"(d[23]),
      "+f"(d[24]), "+f"(d[25]), "+f"(d[26]), "+f"(d[27]), "+f"(d[28]), "+f"(d[29]), "+f"(d[30]), "+f"(d[31]),
      "+f"(d[32]), "+f"(d[33]), "+f"(d[34]), "+f"(d[35]), "+f"(d[36]), "+f"(d[37]), "+f"(d[38]), "+f"(d[39]),
      "+f"(d[40]), "+f"(d[41]), "+f"(d[42]), "+f"(d[43]), "+f"(d[44]), "+f"(d[45]), "+f"(d[46]), "+f"(d[47]),
      "+f"(d[48]), "+f"(d[49]), "+f"(d[50]), "+f"(d[51]), "+f"(d[52]), "+f"(d[53]), "+f"(d[54]), "+f"(d[55]),
      "+f"(d[56]), "+f"(d[57]), "+f"(d[58]), "+f"(d[59]), "+f"(d[60]), "+f"(d[61]), "+f"(d[62]), "+f"(d[63]),
      "+f"(d[64]), "+f"(d[65]), "+f"(d[66]), "+f"(d[67]), "+f"(d[68]), "+f"(d[69]), "+f"(d[70]), "+f"(d[71]),
      "+f"(d[72]), "+f"(d[73]), "+f"(d[74]), "+f"(d[75]), "+f"(d[76]), "+f"(d[77]), "+f"(d[78]), "+f"(d[79])
    : "l"(da), "l"(db), "r"(scale_d), "n"(TA), "n"(TB));
}

__device__ __forceinline__ unsigned load_epoch(int role) {
  unsigned tag;
  asm volatile("ld.relaxed.gpu.global.u32 %0, [%1];" : "=r"(tag) : "l"(g_epoch + role) : "memory");
  return tag;
}

__device__ __forceinline__ int unit_of(int ftype, int nt, int s, bool& ssm) {
  const int c = ftype * 4 + nt;
  ssm = false;
  if (s == 0) return c;
  if (s == 1) { ssm = true; return c; }
  if (s == 2) {
    if (ftype) return 10 + nt;
    if (nt < 2) return 8 + nt;
    ssm = true;
    return 6 + nt;
  }
  if (s == 3) return 14 + c;
  return 23 + nt;
}

template <bool SSM>
__device__ __forceinline__ void unit_mainloop(float (&acc0)[64], float (&acc1)[64], uint32_t sb, int it0, bool first,
                                              bool swap, bool signal, int wg, int lane
) {
  const uint32_t sb16 = (sb & 0x3FFFFu) >> 4;
#pragma unroll 1
  for (int k = 0; k < 10; k++) {
    const int it = it0 + k, s = it & 3;
    if ((threadIdx.x & 127) == 0) TR(it, 2);
    if (first) mbar_wait(sb + B_XFULL + 8 * k, 0);
    mbar_wait(sb + B_FULL1 + 8 * s, (it >> 2) & 1);
    if ((threadIdx.x & 127) == 0) TR(it, 3);
    const uint32_t res = sb16 + (SM_RES >> 4) + k * (CH >> 4), ring = sb16 + (SM_RING >> 4) + s * (CH >> 4);
    const uint32_t xa = swap ? ring : res, wa = swap ? res : ring;
    fence_regs(acc0); fence_regs(acc1);
    wg_fence();
#pragma unroll
    for (int kk = 0; kk < 4; kk++) {
      const int sc = (k | kk) != 0;
      if (SSM) {
        const uint64_t db = desc_k(xa + kk * 2);
        wgmma_n128<0, 0>(acc0, desc_k(wa + kk * 2), db, sc);
        wgmma_n128<0, 0>(acc1, desc_k(wa + 512 + kk * 2), db, sc);
      } else {
        const uint64_t db = desc_mn(wa + kk * 128);
        wgmma_n128<0, 1>(acc0, desc_k(xa + kk * 2), db, sc);
        wgmma_n128<0, 1>(acc1, desc_k(xa + 512 + kk * 2), db, sc);
      }
    }
    wg_commit();
    if (k == 9 && signal) bar_arrive(1 + (wg ^ 1), 256);
    if (k > 0) {
      wg_wait<1>();
      if (lane == 0) mbar_arrive(sb + B_EMPTY1 + 8 * ((it - 1) & 3));
    }
    fence_regs(acc0); fence_regs(acc1);
  }
  wg_wait<0>();
  fence_regs(acc0); fence_regs(acc1);
  if (lane == 0) mbar_arrive(sb + B_EMPTY1 + 8 * ((it0 + 9) & 3));
}

__device__ __forceinline__ void ffn_half(const float (&a)[64], unsigned char* tile, int mh, int w, int lane) {
  const int q = lane & 3, r = lane >> 2;
#pragma unroll
  for (int hi = 0; hi < 2; hi++) {
    const int m7 = 4 * (w & 1) + 2 * hi + (r & 1);
    const int m = (2 * mh + (w >> 1)) * 32 + (r >> 1) * 8 + m7;
    uint32_t p[8];
#pragma unroll
    for (int j = 0; j < 8; j++) {
      float v[2];
#pragma unroll
      for (int e = 0; e < 2; e++) {
        const float g = a[4 * j + 2 * hi + e], u = a[32 + 4 * j + 2 * hi + e];
        v[e] = g * u * fast_rcp(1.0f + fast_ex2(g * -1.4426950408889634f));
      }
      p[j] = pack_bf16(v[0], v[1]);
    }
    unsigned char* row = tile + m * 128;
    st_v4(row + ((q ^ m7) << 4), p[0], p[1], p[2], p[3]);
    st_v4(row + (((4 + q) ^ m7) << 4), p[4], p[5], p[6], p[7]);
  }
}

struct SsmCoef { cplx lam, c, l32, mu; };
__device__ __forceinline__ SsmCoef ssm_coef(const Params& P, int p) {
  const float lr = __bfloat162float(P.lre[p]), li = __bfloat162float(P.lim[p]);
  const float dt = __bfloat162float(__float2bfloat16_rn(expf(__bfloat162float(P.logdt[p]))));
  float sn, cs;
  sincosf(dt * li, &sn, &cs);
  const float ex = expf(dt * lr);
  SsmCoef o;
  o.lam = {ex * cs, ex * sn};
  const float nr = o.lam.r - 1.0f, ni = o.lam.i, den = 1.0f / (lr * lr + li * li);
  o.c = {(nr * lr + ni * li) * den, (ni * lr - nr * li) * den};
  cplx t = o.lam;
#pragma unroll
  for (int i = 0; i < 5; i++) t = cmul(t, t);
  o.l32 = t;
  t = cmul(t, t);
  o.mu = cmul(t, t);
  return o;
}

__device__ __forceinline__ void ssm_epilogue(const float (&vr)[64], const float (&vi)[64], const SsmCoef (&co)[2], int rb,
                                             int cg, unsigned tag, int w, int lane) {
  const int q = lane & 3, r = lane >> 2;
  cplx s[2], init[2];
#pragma unroll
  for (int hi = 0; hi < 2; hi++) s[hi] = {vr[2 * hi], vi[2 * hi]};
#pragma unroll
  for (int t = 1; t < 32; t++)
#pragma unroll
    for (int hi = 0; hi < 2; hi++) {
      const int i = 4 * (t >> 1) + 2 * hi + (t & 1);
      s[hi] = cfma(co[hi].lam, s[hi], cplx{vr[i], vi[i]});
    }
  unsigned long long* agg = g_agg + (size_t)(cg * NRB) * 128;
#pragma unroll
  for (int hi = 0; hi < 2; hi++) {
    const cplx l64 = cmul(co[hi].l32, co[hi].l32);
    cplx y = cshfl_up(s[hi], 1);
    if (q >= 1) s[hi] = cfma(co[hi].l32, y, s[hi]);
    y = cshfl_up(s[hi], 2);
    if (q >= 2) s[hi] = cfma(l64, y, s[hi]);
    if (q == 3 && rb < NRB - 1) {
      const unsigned long long a = ((unsigned long long)tag << 32) | __float_as_uint(s[hi].r);
      const unsigned long long b = ((unsigned long long)tag << 32) | __float_as_uint(s[hi].i);
      asm volatile("st.relaxed.gpu.global.v2.b64 [%0], {%1, %2};" ::"l"(agg + (rb * 64 + 16 * w + r + 8 * hi) * 2), "l"(a), "l"(b) : "memory");
    }
    y = cshfl_up(s[hi], 1);
    init[hi] = q >= 1 ? y : cplx{0.f, 0.f};
  }
  if (rb > 0) {
    cplx e[2][4];
    int spin = 0;
    while (true) {
      bool ok = true;
#pragma unroll
      for (int m = 0; m < 4; m++) {
        const int j = rb - 1 - q - 4 * m;
#pragma unroll
        for (int hi = 0; hi < 2; hi++) {
          unsigned long long a = (unsigned long long)tag << 32, b = a;
          if (j >= 0)
            asm volatile("ld.relaxed.gpu.global.v2.b64 {%0, %1}, [%2];" : "=l"(a), "=l"(b) : "l"(agg + (j * 64 + 16 * w + r + 8 * hi) * 2) : "memory");
          ok = ok && (unsigned)(a >> 32) == tag && (unsigned)(b >> 32) == tag;
          e[hi][m] = {__uint_as_float((unsigned)a), __uint_as_float((unsigned)b)};
        }
      }
      if (__all_sync(0xffffffffu, ok)) break;
      trap_if_over(++spin, 1 << 21);
    }
#pragma unroll
    for (int hi = 0; hi < 2; hi++) {
      const cplx mu = co[hi].mu, mu2 = cmul(mu, mu), mu4 = cmul(mu2, mu2);
      cplx a = cfma(mu4, e[hi][3], e[hi][2]);
      a = cfma(mu4, a, e[hi][1]);
      a = cfma(mu4, a, e[hi][0]);
      if (q & 1) a = cmul(a, mu);
      if (q & 2) a = cmul(a, mu2);
      a.r += __shfl_xor_sync(0xffffffffu, a.r, 1); a.i += __shfl_xor_sync(0xffffffffu, a.i, 1);
      a.r += __shfl_xor_sync(0xffffffffu, a.r, 2); a.i += __shfl_xor_sync(0xffffffffu, a.i, 2);
      if (q & 1) a = cmul(a, co[hi].l32);
      if (q & 2) a = cmul(a, cmul(co[hi].l32, co[hi].l32));
      init[hi].r += a.r; init[hi].i += a.i;
    }
  }
  unsigned char* tile = g_h + (size_t)((rb * NCG + cg) * 2) * CH;
#pragma unroll
  for (int i8 = 0; i8 < 4; i8++) {
    uint32_t pr[2][4], pi[2][4];
#pragma unroll
    for (int jj = 0; jj < 4; jj++) {
#pragma unroll
      for (int hi = 0; hi < 2; hi++) {
        float hr[2], hn[2];
#pragma unroll
        for (int e = 0; e < 2; e++) {
          const int i = 4 * (4 * i8 + jj) + 2 * hi + e;
          init[hi] = cfma(co[hi].lam, init[hi], cplx{vr[i], vi[i]});
          hr[e] = co[hi].c.r * init[hi].r - co[hi].c.i * init[hi].i;
          hn[e] = -co[hi].c.r * init[hi].i - co[hi].c.i * init[hi].r;
        }
        pr[hi][jj] = pack_bf16(hr[0], hr[1]);
        pi[hi][jj] = pack_bf16(hn[0], hn[1]);
      }
    }
#pragma unroll
    for (int hi = 0; hi < 2; hi++) {
      unsigned char* a = tile + (i8 >> 1) * 8192 + (16 * w + 8 * hi + r) * 128 + ((((i8 & 1) * 4 + q) ^ r) << 4);
      st_v4(a, pr[hi][0], pr[hi][1], pr[hi][2], pr[hi][3]);
      st_v4(a + CH, pi[hi][0], pi[hi][1], pi[hi][2], pi[hi][3]);
    }
  }
}

template <bool F>
__device__ __forceinline__ void phase2(const Params& P, uint32_t sb, int rb, int nt, int wg, int w, int lane
) {
  constexpr int NK = F ? NFC : 2 * NCG;
  const int q = lane & 3, r = lane >> 2, warp = wg * 4 + w;
  const int m0 = 64 * wg + 16 * w + r;
  const int mk = m0 + (F ? 8 : 0), ms = m0 + (F ? 0 : 8);
  const int tk = 32 * ((mk >> 3) & 3) + 8 * (mk >> 5) + (mk & 7);
  const int ts = 32 * ((ms >> 3) & 3) + 8 * (ms >> 5) + (ms & 7);
  const int rot = (F && (nt & 1)) ? 2 : 0;
  uint32_t xd[20];
  {
    const __nv_bfloat16* xr = P.xin + (size_t)(rb * 128 + tk) * DM + 160 * nt + 2 * q;
    const __nv_bfloat16* dr = P.dskip + 160 * nt + 2 * q;
#pragma unroll
    for (int j = 0; j < 20; j++) {
      int dj = j + 2 * rot;
      if (dj >= 20) dj -= 20;
      const __nv_bfloat162 a = __ldg((const __nv_bfloat162*)(xr + 8 * dj)), b = __ldg((const __nv_bfloat162*)(dr + 8 * dj));
      const __nv_bfloat162 c = __hmul2(a, b);
      xd[j] = *(const uint32_t*)&c;
    }
  }
  if (lane == 0) mbar_expect_tx(sb + B_RECV + 8 * warp, 5120);
  asm volatile("barrier.cluster.wait.acquire.aligned;" ::: "memory");
  const uint32_t peer = F ? 0 : 1;
  const uint32_t sb16 = (sb & 0x3FFFFu) >> 4;
  float acc[80];
  int s = 0, ph = 0, ps = 0;
  PROF_EV(32 + wg * 8 + 0);
#pragma unroll 1
  for (int k = 0; k < NK; k++) {
    if (threadIdx.x == 128) TR(50 + k, 2);
    { PROF_T0; mbar_wait(sb + B_FULL2 + 8 * s, ph); PROF_ACC(pw); }
    if (threadIdx.x == 128) TR(50 + k, 3);
    const uint32_t a = sb16 + s * (ST2 >> 4) + wg * 512, b = sb16 + s * (ST2 >> 4) + (CH >> 4);
    fence_regs(acc);
    wg_fence();
#pragma unroll
    for (int kk = 0; kk < 4; kk++) {
      const int sc = (k | kk) != 0;
      if (F) wgmma_n160<0, 1>(acc, desc_k(a + kk * 2), desc_mn(b + kk * 128), sc);
      else   wgmma_n160<1, 0>(acc, desc_mn(a + kk * 128), desc_k(b + kk * 2), sc);
    }
    wg_commit();
    if (k > 0) {
      wg_wait<1>();
      if (lane == 0) {
        if (k - 1 < NK - 5) mbar_arrive(sb + B_EMPTY2 + 8 * ps);
        else if (k - 1 == NK - 5) mbar_arrive_remote(mapa(sb + B_PEER, peer));
      }
    }
    fence_regs(acc);
    ps = s;
    if (++s == 5) { s = 0; ph ^= 1; }
  }
  mbar_wait(sb + B_G, 0);
  float gk, gs;
  asm volatile("ld.shared.f32 %0, [%1];" : "=f"(gk) : "r"(sb + SM_G + 4 * tk));
  asm volatile("ld.shared.f32 %0, [%1];" : "=f"(gs) : "r"(sb + SM_G + 4 * ts));
  const float sk = F ? 1.0f - gk : 2.0f * gk, ss = F ? 1.0f - gs : 2.0f * gs;
  mbar_wait_cluster(sb + B_PEER, 0);
  wg_wait<0>();
  fence_regs(acc);
  PROF_EV(32 + wg * 8 + 1);
  constexpr int RSLOT_PEER = F ? (2 * NCG) % 5 : NFC % 5, RSLOT = NK % 5;
  const uint32_t rdst = mapa(sb + RSLOT_PEER * ST2 + warp * 5120 + lane * 16, peer);
  const uint32_t rbar = mapa(sb + B_RECV + 8 * warp, peer);
  constexpr int OS = F ? 0 : 2, OK = F ? 2 : 0;
#pragma unroll
  for (int i = 0; i < 10; i++) {
    int c = i + rot;
    if (c >= 10) c -= 10;
    asm volatile("st.async.weak.shared::cluster.mbarrier::complete_tx::bytes.v4.f32 [%0], {%1, %2, %3, %4}, [%5];"
                 ::"r"(rdst + c * 512), "f"(acc[8 * i + OS] * ss), "f"(acc[8 * i + OS + 1] * ss),
                   "f"(acc[8 * i + 4 + OS] * ss), "f"(acc[8 * i + 4 + OS + 1] * ss), "r"(rbar) : "memory");
  }
  float* orow = P.out + (size_t)(rb * 128 + tk) * DM + 160 * nt + 2 * q;
  mbar_wait_cluster(sb + B_RECV + 8 * warp, 0);
  PROF_EV(32 + wg * 8 + 2);
#pragma unroll
  for (int i = 0; i < 10; i++) {
    int c = i + rot;
    if (c >= 10) c -= 10;
    float4 v;
    asm volatile("ld.shared.v4.f32 {%0, %1, %2, %3}, [%4];" : "=f"(v.x), "=f"(v.y), "=f"(v.z), "=f"(v.w)
                 : "r"(sb + RSLOT * ST2 + warp * 5120 + c * 512 + lane * 16));
    float2 o0, o1;
    o0.x = fmaf(acc[8 * i + OK], sk, fmaf(gk, bf_lo(xd[2 * i]), v.x));
    o0.y = fmaf(acc[8 * i + OK + 1], sk, fmaf(gk, bf_hi(xd[2 * i]), v.y));
    o1.x = fmaf(acc[8 * i + 4 + OK], sk, fmaf(gk, bf_lo(xd[2 * i + 1]), v.z));
    o1.y = fmaf(acc[8 * i + 4 + OK + 1], sk, fmaf(gk, bf_hi(xd[2 * i + 1]), v.w));
    *(float2*)(orow + 16 * c) = o0;
    *(float2*)(orow + 16 * c + 8) = o1;
  }
  PROF_EV(32 + wg * 8 + 3);
}

__global__ void __launch_bounds__(384, 1) __cluster_dims__(2, 1, 1) fused_kernel(const __grid_constant__ Params P) {
  extern __shared__ __align__(1024) unsigned char smem_raw[];
  const uint32_t sb = smem_u32(smem_raw);
  trap_if_over((int)(sb & 1023u), 0);
  const int warp = __shfl_sync(0xffffffffu, threadIdx.x >> 5, 0), lane = threadIdx.x & 31;
  uint32_t ftype, smid;
  asm("mov.u32 %0, %%cluster_ctarank;" : "=r"(ftype));
  asm("mov.u32 %0, %%smid;" : "=r"(smid));
  const int tp = P.use_smid ? (int)(smid >> 1) : (int)(blockIdx.x >> 1);
  int gpc, idx;
  bool extra = false;
  if (tp < 32) { gpc = tp & 7; idx = tp >> 3; }
  else if (tp < 60) { gpc = 1 + (tp - 32) % 7; idx = 4 + (tp - 32) / 7; }
  else if (tp < 62) { gpc = 0; idx = tp - 60; extra = true; }
  else { gpc = 0; idx = tp - 58; }
  const int rb = extra ? (idx * 2 + ftype) * 4 : 2 * gpc + (idx >> 2);
  const int nt = idx & 3;
  const int role = tp * 2 + ftype;
  const int nslots = (extra || ftype) ? 4 : 5;

  if (threadIdx.x == 256) {
    prefetch_map(&P.x); prefetch_map(&P.wg); prefetch_map(&P.wu);
#pragma unroll
    for (int i = 0; i < 38; i++)
      mbar_init(sb + SM_BAR + 8 * i, i < 14 ? 1 : i < 18 ? 4 : i < 23 ? 1 : i < 28 ? 8 : i == 28 ? 64 : i == 29 ? 8 : 1);
    asm volatile("st.shared.u32 [%0], %1;" ::"r"(sb + SM_READY), "r"(0) : "memory");
    asm volatile("fence.mbarrier_init.release.cluster;" ::: "memory");
  }
  __syncthreads();
  asm volatile("barrier.cluster.arrive.relaxed.aligned;" ::: "memory");

  if (warp >= 8) {
    asm volatile("setmaxnreg.dec.sync.aligned.u32 40;");
    if (warp == 8) {
      if (lane == 0) {
        const int n1 = nslots * 10;
        {
          const int fc0 = extra ? EXTRA_FC : ftype * 4 + nt;
          for (int k = 0; k < 10; k++) {
            const uint32_t res = sb + SM_RES + k * CH, ring = sb + SM_RING + k * CH;
            const uint32_t bx = sb + B_XFULL + 8 * k, bf = sb + B_FULL1 + 8 * k;
            mbar_expect_tx(bx, k == 0 ? CH + 1280 : CH);
            if (k < 4) mbar_expect_tx(bf, CH);
            if (!extra) {
              tma5d(res, &P.x, 64 * k, rb, bx);
              if (k < 4) { tma2d(ring, &P.wg, 64 * fc0, 64 * k, bf); tma2d(ring + 8192, &P.wu, 64 * fc0, 64 * k, bf); }
            } else {
              tma2d(res, &P.wg, 64 * fc0, 64 * k, bx); tma2d(res + 8192, &P.wu, 64 * fc0, 64 * k, bx);
              if (k < 4) tma5d(ring, &P.x, 64 * k, rb, bf);
            }
            if (k == 0) bulk_load(sb + SM_GW, P.gatew, 1280, bx);
          }
          prefetch_map(&P.bre); prefetch_map(&P.bim);
          if (ftype) { prefetch_map(&P.wd); prefetch_map(&P.wdw[nt]); } else { prefetch_map(&P.cre); prefetch_map(&P.cim); }
        }
        int slot = 0, k = 4;
        bool ssm = false;
        int id = extra ? 0 : unit_of(ftype, nt, 0, ssm);
        for (int it = 4; it < n1; it++) {
          if (k == 10) { k = 0; slot++; if (!extra) id = unit_of(ftype, nt, slot, ssm); }
          const int s = it & 3;
          const uint32_t ring = sb + SM_RING + s * CH, bf = sb + B_FULL1 + 8 * s;
          { PROF_T0; mbar_wait(sb + B_EMPTY1 + 8 * s, ((it >> 2) & 1) ^ 1); PROF_ACC(pw1); }
          TR(it, 0);
          mbar_expect_tx(bf, CH);
          if (extra) tma5d(ring, &P.x, 64 * k, rb + slot, bf);
          else if (ssm) { tma2d(ring, &P.bre, 64 * k, 64 * id, bf); tma2d(ring + 8192, &P.bim, 64 * k, 64 * id, bf); }
          else { tma2d(ring, &P.wg, 64 * id, 64 * k, bf); tma2d(ring + 8192, &P.wu, 64 * id, 64 * k, bf); }
          TR(it, 1);
          k++;
        }
        if (!extra) {
          const int nk = ftype ? NFC : 2 * NCG;
          const int d0 = 160 * nt + ((nt & 1) ? 32 : 0);
          mbar_wait(sb + B_G, 0);
          int s = 0, ph = 1;
          uint32_t ready = 0;
          for (int k2 = 0; k2 < nk; k2++) {
            if (k2 == 2) { mbar_wait(sb + B_EMPTY1 + 8 * ((n1 - 4) & 3), ((n1 - 4) >> 2) & 1); mbar_wait(sb + B_EMPTY1 + 8 * ((n1 - 3) & 3), ((n1 - 3) >> 2) & 1); }
            if (k2 == 3) { mbar_wait(sb + B_EMPTY1 + 8 * ((n1 - 2) & 3), ((n1 - 2) >> 2) & 1); mbar_wait(sb + B_EMPTY1 + 8 * ((n1 - 1) & 3), ((n1 - 1) >> 2) & 1); }
            if (k2 >= 5) { PROF_T0; mbar_wait(sb + B_EMPTY2 + 8 * s, ph); PROF_ACC(pw2); }
            TR(50 + k2, 0);
            const uint32_t st = sb + s * ST2, bf = sb + B_FULL2 + 8 * s;
            const uint32_t need = ftype ? k2 : (k2 >> 1);
            mbar_expect_tx(bf, ftype ? 40960 : 36864);
            if (ftype) {
              tma5d(st + CH, &P.wd, d0, 2 * k2, bf);
              tma5d(st + CH + 8192, &P.wd, d0 + 64, 2 * k2, bf);
              tma5d(st + CH + 16384, &P.wdw[nt], 0, 2 * k2, bf);
            } else {
              tma2d(st + CH, (k2 & 1) ? &P.cim : &P.cre, 64 * (k2 >> 1), 160 * nt, bf);
            }
            if (ready <= need) {
              int spin = 0;
              PROF_T0;
              do {
                asm volatile("ld.acquire.cta.shared.u32 %0, [%1];" : "=r"(ready) : "r"(sb + SM_READY) : "memory");
                trap_if_over(++spin, 1 << 26);
              } while (ready <= need);
              asm volatile("fence.proxy.async.global;" ::: "memory");
              PROF_ACC(pw3);
            }
            bulk_load(st, ftype ? g_act + (size_t)(rb * NFC + k2) * CH : g_h + (size_t)(rb * 2 * NCG + k2) * CH, CH, bf);
            TR(50 + k2, 1);
            if (++s == 5) { s = 0; ph ^= 1; }
          }
        }
      }
    } else if (warp == 9) {
      const unsigned want = load_epoch(role) + 1;
      if (!extra) {
        mbar_wait(sb + B_XFULL + 8 * 9, 0);
        if (lane == 0) {
          const int pc = (rb * 4 + nt) * 2 + ftype;
          l2_prefetch(P.p_cre + pc * 6400, 6400);
          l2_prefetch(P.p_cim + pc * 6400, 6400);
          l2_prefetch(P.p_wd + pc * 17280, 17280);
        }
      }
      for (int slot = 0; slot < nslots; slot++) {
        bool ssm = false;
        const int id = extra ? EXTRA_FC : unit_of(ftype, nt, slot, ssm);
        bar_sync(3 + ((slot + nslots) & 1), 160);
        if (lane == 0) {
          asm volatile("fence.acq_rel.gpu;" ::: "memory");
          asm volatile("st.relaxed.gpu.global.u32 [%0], %1;" ::"l"((ssm ? g_flag_h : g_flag_act) + (extra ? rb + slot : rb) * 32 + id), "r"(want) : "memory");
        }
        __syncwarp();
      }
    } else if (!extra) {
      const unsigned want = load_epoch(role) + 1;
      const int r0 = (warp - 10) * 64 + lane;
      float a0 = 0.f, a1 = 0.f;
#pragma unroll 1
      for (int k = 0; k < 10; k++) {
        mbar_wait(sb + B_XFULL + 8 * k, 0);
#pragma unroll 2
        for (int c = 0; c < 8; c++) {
          uint4 gw, u, v;
          const uint32_t ad = sb + SM_RES + k * CH + r0 * 128 + ((c ^ (r0 & 7)) << 4);
          asm volatile("ld.shared.v4.u32 {%0, %1, %2, %3}, [%4];" : "=r"(gw.x), "=r"(gw.y), "=r"(gw.z), "=r"(gw.w) : "r"(sb + SM_GW + 128 * k + 16 * c));
          asm volatile("ld.shared.v4.u32 {%0, %1, %2, %3}, [%4];" : "=r"(u.x), "=r"(u.y), "=r"(u.z), "=r"(u.w) : "r"(ad));
          asm volatile("ld.shared.v4.u32 {%0, %1, %2, %3}, [%4];" : "=r"(v.x), "=r"(v.y), "=r"(v.z), "=r"(v.w) : "r"(ad + 32 * 128));
          const uint32_t gg[4] = {gw.x, gw.y, gw.z, gw.w}, uu[4] = {u.x, u.y, u.z, u.w}, vv[4] = {v.x, v.y, v.z, v.w};
#pragma unroll
          for (int i = 0; i < 4; i++) {
            a0 = fmaf(bf_lo(uu[i]), bf_lo(gg[i]), fmaf(bf_hi(uu[i]), bf_hi(gg[i]), a0));
            a1 = fmaf(bf_lo(vv[i]), bf_lo(gg[i]), fmaf(bf_hi(vv[i]), bf_hi(gg[i]), a1));
          }
        }
      }
      const int r1 = r0 + 32;
      const int t0 = 32 * ((r0 >> 1) & 3) + 2 * (r0 >> 3) + (r0 & 1), t1 = 32 * ((r1 >> 1) & 3) + 2 * (r1 >> 3) + (r1 & 1);
      asm volatile("st.shared.f32 [%0], %1;" ::"r"(sb + SM_G + 4 * t0), "f"(1.0f / (1.0f + expf(-a0))) : "memory");
      asm volatile("st.shared.f32 [%0], %1;" ::"r"(sb + SM_G + 4 * t1), "f"(1.0f / (1.0f + expf(-a1))) : "memory");
      mbar_arrive(sb + B_G);
      if (warp == 11) {
        const int nf = ftype ? NFC : NCG;
        const unsigned* fl = (ftype ? g_flag_act : g_flag_h) + rb * 32 + lane;
        uint32_t last = 0;
        int spin = 0;
        while (last < (uint32_t)nf) {
          unsigned v = want;
          if (lane < nf) asm volatile("ld.acquire.gpu.global.u32 %0, [%1];" : "=r"(v) : "l"(fl) : "memory");
          const unsigned miss = __ballot_sync(0xffffffffu, v != want);
          const uint32_t n = miss ? __ffs(miss) - 1 : 32;
          __syncwarp();
          if (n > last) {
            last = n;
            if (lane == 0) asm volatile("st.release.cta.shared.u32 [%0], %1;" ::"r"(sb + SM_READY), "r"(n) : "memory");
          } else {
            __nanosleep(200);
          }
          trap_if_over(++spin, 1 << 22);
        }
      }
    }
    __syncwarp();
    asm volatile("barrier.cluster.wait.acquire.aligned;" ::: "memory");
  } else {
    asm volatile("setmaxnreg.inc.sync.aligned.u32 232;");
    const int wg = warp >> 2, w = warp & 3;
    const unsigned tag = load_epoch(role);
    bool first = true;
#pragma unroll 1
    for (int slot = (wg + nslots) & 1; slot < nslots; slot += 2) {
      bool ssm = false;
      const int id = extra ? EXTRA_FC : unit_of(ftype, nt, slot, ssm);
      const bool signal = slot + 1 < nslots;
      float acc0[64], acc1[64];
      if (ssm) {
        SsmCoef co[2];
        co[0] = ssm_coef(P, 64 * id + 16 * w + (lane >> 2));
        co[1] = ssm_coef(P, 64 * id + 16 * w + (lane >> 2) + 8);
        bar_sync(1 + wg, 256);
        PROF_EV(slot * 4 + 0);
        unit_mainloop<true>(acc0, acc1, sb, slot * 10, first, false, signal, wg, lane PROF_ARGS);
        PROF_EV(slot * 4 + 1);
        ssm_epilogue(acc0, acc1, co, rb, id, tag + 1, w, lane);
        PROF_EV(slot * 4 + 2);
        bar_arrive(3 + wg, 160);
      } else {
        if (slot > 0) bar_sync(1 + wg, 256);
        PROF_EV(slot * 4 + 0);
        unit_mainloop<false>(acc0, acc1, sb, slot * 10, first, extra, signal, wg, lane PROF_ARGS);
        PROF_EV(slot * 4 + 1);
        const int rbo = extra ? rb + slot : rb;
        unsigned char* tile = g_act + (size_t)(rbo * NFC + id) * CH;
        ffn_half(acc0, tile, 0, w, lane);
        ffn_half(acc1, tile, 1, w, lane);
        PROF_EV(slot * 4 + 2);
        bar_arrive(3 + wg, 160);
      }
      PROF_EV(slot * 4 + 3);
      first = false;
    }
    if (extra) {
      asm volatile("barrier.cluster.wait.acquire.aligned;" ::: "memory");
    } else {
      if (ftype) phase2<true>(P, sb, rb, nt, wg, w, lane);
      else phase2<false>(P, sb, rb, nt, wg, w, lane);
    }
    bar_sync(5, 256);
    if (threadIdx.x == 0) g_epoch[role] = tag + 1;
  }
}

typedef CUresult (*EncodeFn)(CUtensorMap*, CUtensorMapDataType, cuuint32_t, void*, const cuuint64_t*, const cuuint64_t*,
                             const cuuint32_t*, const cuuint32_t*, CUtensorMapInterleave, CUtensorMapSwizzle,
                             CUtensorMapL2promotion, CUtensorMapFloatOOBfill);

void encode(EncodeFn fn, CUtensorMap* m, const void* base, int rank, const cuuint64_t* dims, const cuuint64_t* strides,
            const cuuint32_t* box) {
  const cuuint32_t es[5] = {1, 1, 1, 1, 1};
  fn(m, CU_TENSOR_MAP_DATA_TYPE_BFLOAT16, rank, const_cast<void*>(base), dims, strides, box, es,
     CU_TENSOR_MAP_INTERLEAVE_NONE, CU_TENSOR_MAP_SWIZZLE_128B, CU_TENSOR_MAP_L2_PROMOTION_L2_128B,
     CU_TENSOR_MAP_FLOAT_OOB_FILL_NONE);
}

}

extern "C" void kernel_launch(void* const* d_in, const int* in_sizes, int n_in, void* d_out, int out_size) {
  (void)in_sizes; (void)n_in; (void)out_size;
  static EncodeFn enc = nullptr;
  static int sms = 0;
  if (!enc) {
    void* fn = nullptr;
    cudaDriverEntryPointQueryResult qr;
    cudaGetDriverEntryPoint("cuTensorMapEncodeTiled", &fn, cudaEnableDefault, &qr);
    enc = (EncodeFn)fn;
    int dev = 0;
    cudaGetDevice(&dev);
    cudaDeviceGetAttribute(&sms, cudaDevAttrMultiProcessorCount, dev);
    cudaFuncSetAttribute(fused_kernel, cudaFuncAttributeMaxDynamicSharedMemorySize, SMEM_BYTES);
  }
  typedef const __nv_bfloat16* bp;
  Params P;
  const cuuint64_t R = DM * 2;
  {
    const cuuint64_t d[5] = {DM, 2, 4, 16, NRB}, s[4] = {R, 32 * R, 2 * R, 128 * R};
    const cuuint32_t b[5] = {64, 2, 4, 16, 1};
    encode(enc, &P.x, d_in[0], 5, d, s, b);
  }
  {
    const cuuint64_t d[2] = {DM, DM}, s[1] = {R};
    const cuuint32_t b[2] = {64, 64}, bc[2] = {64, 160};
    encode(enc, &P.bre, d_in[3], 2, d, s, b);
    encode(enc, &P.bim, d_in[4], 2, d, s, b);
    encode(enc, &P.cre, d_in[5], 2, d, s, bc);
    encode(enc, &P.cim, d_in[6], 2, d, s, bc);
  }
  {
    const cuuint64_t d[2] = {FF, DM}, s[1] = {FF * 2};
    const cuuint32_t b[2] = {64, 64};
    encode(enc, &P.wg, d_in[10], 2, d, s, b);
    encode(enc, &P.wu, d_in[11], 2, d, s, b);
  }
  {
    cuuint64_t d[5] = {DM, 2, 4, 4, FF / 32};
    const cuuint64_t s[4] = {R, 8 * R, 2 * R, 32 * R};
    const cuuint32_t b[5] = {64, 2, 4, 4, 2};
    encode(enc, &P.wd, d_in[12], 5, d, s, b);
    d[0] = 32;
    for (int nt = 0; nt < 4; nt++) encode(enc, &P.wdw[nt], (bp)d_in[12] + 160 * nt + ((nt & 1) ? 0 : 128), 5, d, s, b);
  }
  P.xin = (bp)d_in[0]; P.lre = (bp)d_in[1]; P.lim = (bp)d_in[2]; P.logdt = (bp)d_in[7]; P.dskip = (bp)d_in[8];
  P.gatew = (bp)d_in[13];
  P.p_bre = (const char*)d_in[3]; P.p_bim = (const char*)d_in[4]; P.p_cre = (const char*)d_in[5]; P.p_cim = (const char*)d_in[6];
  P.p_wg = (const char*)d_in[10]; P.p_wu = (const char*)d_in[11]; P.p_wd = (const char*)d_in[12];
  P.out = (float*)d_out;
  P.use_smid = sms == 132;
  fused_kernel<<<132, 384, SMEM_BYTES, cudaStreamPerThread>>>(P);
}
```

```cpp
#include <cuda_runtime.h>
#include <cuda_bf16.h>
#include <cuda.h>
#include <stdint.h>

namespace {

constexpr int DM = 640, FF = 1728;
constexpr int NRB = 16;
constexpr int NFC = 27;
constexpr int NCG = 10;
constexpr int CH = 16384;
constexpr int EXTRA_FC = 22;

constexpr int SM_RES = 0;
constexpr int SM_RING = 10 * CH;
constexpr int ST2 = 40960;
constexpr int SM_BAR = 14 * CH;
constexpr int B_XFULL = SM_BAR;
constexpr int B_FULL1 = B_XFULL + 80;
constexpr int B_EMPTY1 = B_FULL1 + 32;
constexpr int B_FULL2 = B_EMPTY1 + 32;
constexpr int B_EMPTY2 = B_FULL2 + 40;
constexpr int B_G = B_EMPTY2 + 40;
constexpr int B_PEER = B_G + 8;
constexpr int B_RECV = B_PEER + 8;
constexpr int SM_READY = B_RECV + 64;
constexpr int SM_G = SM_BAR + 512;
constexpr int SM_GW = SM_BAR + 1024;
constexpr int SMEM_BYTES = SM_GW + 1280 + 768;

struct Params {
  CUtensorMap x, bre, bim, wg, wu, cre, cim, wd, wdw[4];
  const __nv_bfloat16 *xin, *lre, *lim, *logdt, *dskip, *gatew;
  const char *p_cre, *p_cim, *p_wd, *p_wg, *p_wu, *p_bre, *p_bim;
  float* out;
  int use_smid;
};

__device__ __align__(1024) unsigned char g_act[NRB * NFC * CH];
__device__ __align__(1024) unsigned char g_h[NRB * NCG * 2 * CH];
__device__ __align__(16) unsigned long long g_agg[NCG * NRB * 64 * 2];
__device__ unsigned g_flag_act[NRB * 32];
__device__ unsigned g_flag_h[NRB * 32];
__device__ unsigned g_epoch[132];
#define PROF_EV(i)
#define TR(it, f)
#define PROF_ARGS
#define PROF_T0
#define PROF_ACC(v)

__device__ __forceinline__ uint32_t smem_u32(const void* p) { return (uint32_t)__cvta_generic_to_shared(p); }
__device__ __forceinline__ void mbar_init(uint32_t bar, uint32_t cnt) {
  asm volatile("mbarrier.init.shared::cta.b64 [%0], %1;" ::"r"(bar), "r"(cnt) : "memory");
}
__device__ __forceinline__ void mbar_expect_tx(uint32_t bar, uint32_t bytes) {
  asm volatile("mbarrier.arrive.expect_tx.shared::cta.b64 _, [%0], %1;" ::"r"(bar), "r"(bytes) : "memory");
}
__device__ __forceinline__ void mbar_arrive(uint32_t bar) {
  asm volatile("mbarrier.arrive.shared::cta.b64 _, [%0];" ::"r"(bar) : "memory");
}
__device__ __forceinline__ uint32_t mapa(uint32_t addr, uint32_t cta) {
  uint32_t r;
  asm("mapa.shared::cluster.u32 %0, %1, %2;" : "=r"(r) : "r"(addr), "r"(cta));
  return r;
}
__device__ __forceinline__ void mbar_arrive_remote(uint32_t cluster_bar) {
  asm volatile("mbarrier.arrive.relaxed.cluster.shared::cluster.b64 _, [%0];" ::"r"(cluster_bar) : "memory");
}
__device__ __forceinline__ void mbar_wait(uint32_t bar, uint32_t parity) {
  asm volatile("{\n.reg .pred p;\n.reg .u32 c;\nmov.u32 c, 0;\n"
               "W:\nmbarrier.try_wait.parity.shared::cta.b64 p, [%0], %1;\n@p bra D;\n"
               "add.u32 c, c, 1;\nsetp.gt.u32 p, c, 1048576;\n@p trap;\nbra W;\nD:\n}"
               ::"r"(bar), "r"(parity) : "memory");
}
__device__ __forceinline__ void mbar_wait_cluster(uint32_t bar, uint32_t parity) {
  asm volatile("{\n.reg .pred p;\n.reg .u32 c;\nmov.u32 c, 0;\n"
               "W:\nmbarrier.try_wait.parity.acquire.cluster.shared::cta.b64 p, [%0], %1;\n@p bra D;\n"
               "add.u32 c, c, 1;\nsetp.gt.u32 p, c, 1048576;\n@p trap;\nbra W;\nD:\n}"
               ::"r"(bar), "r"(parity) : "memory");
}
__device__ __forceinline__ void trap_if_over(int n, int limit) {
  asm volatile("{\n.reg .pred p;\nsetp.gt.s32 p, %0, %1;\n@p trap;\n}" ::"r"(n), "r"(limit));
}
__device__ __forceinline__ void bulk_load(uint32_t dst, const void* src, uint32_t bytes, uint32_t bar) {
  asm volatile("cp.async.bulk.shared::cluster.global.mbarrier::complete_tx::bytes [%0], [%1], %2, [%3];"
               ::"r"(dst), "l"(src), "r"(bytes), "r"(bar) : "memory");
}
__device__ __forceinline__ void tma2d(uint32_t dst, const CUtensorMap* m, int c0, int c1, uint32_t bar) {
  asm volatile("cp.async.bulk.tensor.2d.shared::cluster.global.mbarrier::complete_tx::bytes [%0], [%1, {%3, %4}], [%2];"
               ::"r"(dst), "l"(m), "r"(bar), "r"(c0), "r"(c1) : "memory");
}
__device__ __forceinline__ void tma5d(uint32_t dst, const CUtensorMap* m, int c0, int c4, uint32_t bar) {
  asm volatile("cp.async.bulk.tensor.5d.shared::cluster.global.mbarrier::complete_tx::bytes [%0], [%1, {%3, %5, %5, %5, %4}], [%2];"
               ::"r"(dst), "l"(m), "r"(bar), "r"(c0), "r"(c4), "r"(0) : "memory");
}
__device__ __forceinline__ void l2_prefetch(const void* p, uint32_t bytes) {
  asm volatile("cp.async.bulk.prefetch.L2.global [%0], %1;" ::"l"(p), "r"(bytes) : "memory");
}
__device__ __forceinline__ void prefetch_map(const CUtensorMap* m) {
  asm volatile("prefetch.tensormap [%0];" ::"l"(m) : "memory");
}
__device__ __forceinline__ void wg_fence() { asm volatile("wgmma.fence.sync.aligned;" ::: "memory"); }
__device__ __forceinline__ void wg_commit() { asm volatile("wgmma.commit_group.sync.aligned;" ::: "memory"); }
template <int N> __device__ __forceinline__ void wg_wait() { asm volatile("wgmma.wait_group.sync.aligned %0;" ::"n"(N) : "memory"); }
template <int R> __device__ __forceinline__ void fence_regs(float (&d)[R]) {
#pragma unroll
  for (int i = 0; i < R; i++) asm volatile("" : "+f"(d[i])::"memory");
}
__device__ __forceinline__ uint64_t desc_k(uint32_t a16) { return ((uint64_t)0x40000040u << 32) | (uint64_t)(a16 + (1u << 16)); }
__device__ __forceinline__ uint64_t desc_mn(uint32_t a16) { return ((uint64_t)0x40000040u << 32) | (uint64_t)(a16 + (512u << 16)); }
__device__ __forceinline__ void bar_sync(int id, int n) { asm volatile("bar.sync %0, %1;" ::"r"(id), "r"(n) : "memory"); }
__device__ __forceinline__ void bar_arrive(int id, int n) { asm volatile("bar.arrive %0, %1;" ::"r"(id), "r"(n) : "memory"); }
__device__ __forceinline__ uint32_t pack_bf16(float lo, float hi) {
  uint32_t r;
  asm("cvt.rn.bf16x2.f32 %0, %1, %2;" : "=r"(r) : "f"(hi), "f"(lo));
  return r;
}
__device__ __forceinline__ float bf_lo(uint32_t v) { return __uint_as_float(v << 16); }
__device__ __forceinline__ float bf_hi(uint32_t v) { return __uint_as_float(v & 0xFFFF0000u); }
__device__ __forceinline__ void st_v4(void* p, uint32_t a, uint32_t b, uint32_t c, uint32_t d) {
  asm volatile("st.global.v4.b32 [%0], {%1, %2, %3, %4};" ::"l"(p), "r"(a), "r"(b), "r"(c), "r"(d) : "memory");
}
__device__ __forceinline__ float fast_ex2(float x) { float y; asm("ex2.approx.ftz.f32 %0, %1;" : "=f"(y) : "f"(x)); return y; }
__device__ __forceinline__ float fast_rcp(float x) { float y; asm("rcp.approx.ftz.f32 %0, %1;" : "=f"(y) : "f"(x)); return y; }
struct cplx { float r, i; };
__device__ __forceinline__ cplx cmul(cplx a, cplx b) { return {a.r * b.r - a.i * b.i, a.r * b.i + a.i * b.r}; }
__device__ __forceinline__ cplx cfma(cplx a, cplx b, cplx c) {
  return {fmaf(a.r, b.r, fmaf(-a.i, b.i, c.r)), fmaf(a.r, b.i, fmaf(a.i, b.r, c.i))};
}
__device__ __forceinline__ cplx cshfl_up(cplx a, int d) {
  return {__shfl_up_sync(0xffffffffu, a.r, d, 4), __shfl_up_sync(0xffffffffu, a.i, d, 4)};
}

template <int TA, int TB>
__device__ __forceinline__ void wgmma_n128(float (&d)[64], uint64_t da, uint64_t db, int scale_d) {
  asm volatile("{\n.reg .pred p;\nsetp.ne.b32 p, %66, 0;\n"
    "wgmma.mma_async.sync.aligned.m64n128k16.f32.bf16.bf16 {"
    "%0, %1, %2, %3, %4, %5, %6, %7, %8, %9, %10, %11, %12, %13, %14, %15, "
    "%16, %17, %18, %19, %20, %21, %22, %23, %24, %25, %26, %27, %28, %29, %30, %31, "
    "%32, %33, %34, %35, %36, %37, %38, %39, %40, %41, %42, %43, %44, %45, %46, %47, "
    "%48, %49, %50, %51, %52, %53, %54, %55, %56, %57, %58, %59, %60, %61, %62, %63"
    "}, %64, %65, p, 1, 1, %67, %68;\n}\n"
    : "+f"(d[0]), "+f"(d[1]), "+f"(d[2]), "+f"(d[3]), "+f"(d[4]), "+f"(d[5]), "+f"(d[6]), "+f"(d[7]),
      "+f"(d[8]), "+f"(d[9]), "+f"(d[10]), "+f"(d[11]), "+f"(d[12]), "+f"(d[13]), "+f"(d[14]), "+f"(d[15]),
      "+f"(d[16]), "+f"(d[17]), "+f"(d[18]), "+f"(d[19]), "+f"(d[20]), "+f"(d[21]), "+f"(d[22]), "+f"(d[23]),
      "+f"(d[24]), "+f"(d[25]), "+f"(d[26]), "+f"(d[27]), "+f"(d[28]), "+f"(d[29]), "+f"(d[30]), "+f"(d[31]),
      "+f"(d[32]), "+f"(d[33]), "+f"(d[34]), "+f"(d[35]), "+f"(d[36]), "+f"(d[37]), "+f"(d[38]), "+f"(d[39]),
      "+f"(d[40]), "+f"(d[41]), "+f"(d[42]), "+f"(d[43]), "+f"(d[44]), "+f"(d[45]), "+f"(d[46]), "+f"(d[47]),
      "+f"(d[48]), "+f"(d[49]), "+f"(d[50]), "+f"(d[51]), "+f"(d[52]), "+f"(d[53]), "+f"(d[54]), "+f"(d[55]),
      "+f"(d[56]), "+f"(d[57]), "+f"(d[58]), "+f"(d[59]), "+f"(d[60]), "+f"(d[61]), "+f"(d[62]), "+f"(d[63])
    : "l"(da), "l"(db), "r"(scale_d), "n"(TA), "n"(TB));
}

template <int TA, int TB>
__device__ __forceinline__ void wgmma_n160(float (&d)[80], uint64_t da, uint64_t db, int scale_d) {
  asm volatile("{\n.reg .pred p;\nsetp.ne.b32 p, %82, 0;\n"
    "wgmma.mma_async.sync.aligned.m64n160k16.f32.bf16.bf16 {"
    "%0, %1, %2, %3, %4, %5, %6, %7, %8, %9, %10, %11, %12, %13, %14, %15, "
    "%16, %17, %18, %19, %20, %21, %22, %23, %24, %25, %26, %27, %28, %29, %30, %31, "
    "%32, %33, %34, %35, %36, %37, %38, %39, %40, %41, %42, %43, %44, %45, %46, %47, "
    "%48, %49, %50, %51, %52, %53, %54, %55, %56, %57, %58, %59, %60, %61, %62, %63, "
    "%64, %65, %66, %67, %68, %69, %70, %71, %72, %73, %74, %75, %76, %77, %78, %79"
    "}, %80, %81, p, 1, 1, %83, %84;\n}\n"
    : "+f"(d[0]), "+f"(d[1]), "+f"(d[2]), "+f"(d[3]), "+f"(d[4]), "+f"(d[5]), "+f"(d[6]), "+f"(d[7]),
      "+f"(d[8]), "+f"(d[9]), "+f"(d[10]), "+f"(d[11]), "+f"(d[12]), "+f"(d[13]), "+f"(d[14]), "+f"(d[15]),
      "+f"(d[16]), "+f"(d[17]), "+f"(d[18]), "+f"(d[19]), "+f"(d[20]), "+f"(d[21]), "+f"(d[22]), "+f"(d[23]),
      "+f"(d[24]), "+f"(d[25]), "+f"(d[26]), "+f"(d[27]), "+f"(d[28]), "+f"(d[29]), "+f"(d[30]), "+f"(d[31]),
      "+f"(d[32]), "+f"(d[33]), "+f"(d[34]), "+f"(d[35]), "+f"(d[36]), "+f"(d[37]), "+f"(d[38]), "+f"(d[39]),
      "+f"(d[40]), "+f"(d[41]), "+f"(d[42]), "+f"(d[43]), "+f"(d[44]), "+f"(d[45]), "+f"(d[46]), "+f"(d[47]),
      "+f"(d[48]), "+f"(d[49]), "+f"(d[50]), "+f"(d[51]), "+f"(d[52]), "+f"(d[53]), "+f"(d[54]), "+f"(d[55]),
      "+f"(d[56]), "+f"(d[57]), "+f"(d[58]), "+f"(d[59]), "+f"(d[60]), "+f"(d[61]), "+f"(d[62]), "+f"(d[63]),
      "+f"(d[64]), "+f"(d[65]), "+f"(d[66]), "+f"(d[67]), "+f"(d[68]), "+f"(d[69]), "+f"(d[70]), "+f"(d[71]),
      "+f"(d[72]), "+f"(d[73]), "+f"(d[74]), "+f"(d[75]), "+f"(d[76]), "+f"(d[77]), "+f"(d[78]), "+f"(d[79])
    : "l"(da), "l"(db), "r"(scale_d), "n"(TA), "n"(TB));
}

__device__ __forceinline__ unsigned load_epoch(int role) {
  unsigned tag;
  asm volatile("ld.relaxed.gpu.global.u32 %0, [%1];" : "=r"(tag) : "l"(g_epoch + role) : "memory");
  return tag;
}

__device__ __forceinline__ int unit_of(int ftype, int nt, int s, bool& ssm) {
  const int c = ftype * 4 + nt;
  ssm = false;
  if (s == 0) return c;
  if (s == 1) { ssm = true; return c; }
  if (s == 2) {
    if (ftype) return 10 + nt;
    if (nt < 2) return 8 + nt;
    ssm = true;
    return 6 + nt;
  }
  if (s == 3) return 14 + c;
  return 23 + nt;
}

template <bool SSM>
__device__ __forceinline__ void unit_mainloop(float (&acc0)[64], float (&acc1)[64], uint32_t sb, int it0, bool first,
                                              bool swap, bool signal, int wg, int lane
) {
  const uint32_t sb16 = (sb & 0x3FFFFu) >> 4;
#pragma unroll 1
  for (int k = 0; k < 10; k++) {
    const int it = it0 + k, s = it & 3;
    if ((threadIdx.x & 127) == 0) TR(it, 1);
    if (first) mbar_wait(sb + B_XFULL + 8 * k, 0);
    mbar_wait(sb + B_FULL1 + 8 * s, (it >> 2) & 1);
    if ((threadIdx.x & 127) == 0) TR(it, 2);
    const uint32_t res = sb16 + (SM_RES >> 4) + k * (CH >> 4), ring = sb16 + (SM_RING >> 4) + s * (CH >> 4);
    const uint32_t xa = swap ? ring : res, wa = swap ? res : ring;
    fence_regs(acc0); fence_regs(acc1);
    wg_fence();
#pragma unroll
    for (int kk = 0; kk < 4; kk++) {
      const int sc = (k | kk) != 0;
      if (SSM) {
        const uint64_t db = desc_k(xa + kk * 2);
        wgmma_n128<0, 0>(acc0, desc_k(wa + kk * 2), db, sc);
        wgmma_n128<0, 0>(acc1, desc_k(wa + 512 + kk * 2), db, sc);
      } else {
        const uint64_t db = desc_mn(wa + kk * 128);
        wgmma_n128<0, 1>(acc0, desc_k(xa + kk * 2), db, sc);
        wgmma_n128<0, 1>(acc1, desc_k(xa + 512 + kk * 2), db, sc);
      }
    }
    wg_commit();
    if (k == 9 && signal) bar_arrive(1 + (wg ^ 1), 256);
    if (k > 0) {
      wg_wait<1>();
      if (lane == 0) mbar_arrive(sb + B_EMPTY1 + 8 * ((it - 1) & 3));
    }
    fence_regs(acc0); fence_regs(acc1);
  }
  wg_wait<0>();
  fence_regs(acc0); fence_regs(acc1);
  if (lane == 0) mbar_arrive(sb + B_EMPTY1 + 8 * ((it0 + 9) & 3));
}

__device__ __forceinline__ void ffn_half(const float (&a)[64], unsigned char* tile, int mh, int w, int lane) {
  const int q = lane & 3, r = lane >> 2;
#pragma unroll
  for (int hi = 0; hi < 2; hi++) {
    const int m7 = 4 * (w & 1) + 2 * hi + (r & 1);
    const int m = (2 * mh + (w >> 1)) * 32 + (r >> 1) * 8 + m7;
    uint32_t p[8];
#pragma unroll
    for (int j = 0; j < 8; j++) {
      float v[2];
#pragma unroll
      for (int e = 0; e < 2; e++) {
        const float g = a[4 * j + 2 * hi + e], u = a[32 + 4 * j + 2 * hi + e];
        v[e] = g * u * fast_rcp(1.0f + fast_ex2(g * -1.4426950408889634f));
      }
      p[j] = pack_bf16(v[0], v[1]);
    }
    unsigned char* row = tile + m * 128;
    st_v4(row + ((q ^ m7) << 4), p[0], p[1], p[2], p[3]);
    st_v4(row + (((4 + q) ^ m7) << 4), p[4], p[5], p[6], p[7]);
  }
}

struct SsmCoef { cplx lam, c, l32, mu; };
__device__ __forceinline__ SsmCoef ssm_coef(const Params& P, int p) {
  const float lr = __bfloat162float(P.lre[p]), li = __bfloat162float(P.lim[p]);
  const float dt = __bfloat162float(__float2bfloat16_rn(expf(__bfloat162float(P.logdt[p]))));
  float sn, cs;
  sincosf(dt * li, &sn, &cs);
  const float ex = expf(dt * lr);
  SsmCoef o;
  o.lam = {ex * cs, ex * sn};
  const float nr = o.lam.r - 1.0f, ni = o.lam.i, den = 1.0f / (lr * lr + li * li);
  o.c = {(nr * lr + ni * li) * den, (ni * lr - nr * li) * den};
  cplx t = o.lam;
#pragma unroll
  for (int i = 0; i < 5; i++) t = cmul(t, t);
  o.l32 = t;
  t = cmul(t, t);
  o.mu = cmul(t, t);
  return o;
}

__device__ __forceinline__ void ssm_epilogue(const float (&vr)[64], const float (&vi)[64], const SsmCoef (&co)[2], int rb,
                                             int cg, unsigned tag, int w, int lane) {
  const int q = lane & 3, r = lane >> 2;
  cplx s[2], init[2];
#pragma unroll
  for (int hi = 0; hi < 2; hi++) s[hi] = {vr[2 * hi], vi[2 * hi]};
#pragma unroll
  for (int t = 1; t < 32; t++)
#pragma unroll
    for (int hi = 0; hi < 2; hi++) {
      const int i = 4 * (t >> 1) + 2 * hi + (t & 1);
      s[hi] = cfma(co[hi].lam, s[hi], cplx{vr[i], vi[i]});
    }
  unsigned long long* agg = g_agg + (size_t)(cg * NRB) * 128;
#pragma unroll
  for (int hi = 0; hi < 2; hi++) {
    const cplx l64 = cmul(co[hi].l32, co[hi].l32);
    cplx y = cshfl_up(s[hi], 1);
    if (q >= 1) s[hi] = cfma(co[hi].l32, y, s[hi]);
    y = cshfl_up(s[hi], 2);
    if (q >= 2) s[hi] = cfma(l64, y, s[hi]);
    if (q == 3 && rb < NRB - 1) {
      const unsigned long long a = ((unsigned long long)tag << 32) | __float_as_uint(s[hi].r);
      const unsigned long long b = ((unsigned long long)tag << 32) | __float_as_uint(s[hi].i);
      asm volatile("st.relaxed.gpu.global.v2.b64 [%0], {%1, %2};" ::"l"(agg + (rb * 64 + 16 * w + r + 8 * hi) * 2), "l"(a), "l"(b) : "memory");
    }
    y = cshfl_up(s[hi], 1);
    init[hi] = q >= 1 ? y : cplx{0.f, 0.f};
  }
  if (rb > 0) {
    cplx e[2][4];
    int spin = 0;
    while (true) {
      bool ok = true;
#pragma unroll
      for (int m = 0; m < 4; m++) {
        const int j = rb - 1 - q - 4 * m;
#pragma unroll
        for (int hi = 0; hi < 2; hi++) {
          unsigned long long a = (unsigned long long)tag << 32, b = a;
          if (j >= 0)
            asm volatile("ld.relaxed.gpu.global.v2.b64 {%0, %1}, [%2];" : "=l"(a), "=l"(b) : "l"(agg + (j * 64 + 16 * w + r + 8 * hi) * 2) : "memory");
          ok = ok && (unsigned)(a >> 32) == tag && (unsigned)(b >> 32) == tag;
          e[hi][m] = {__uint_as_float((unsigned)a), __uint_as_float((unsigned)b)};
        }
      }
      if (__all_sync(0xffffffffu, ok)) break;
      trap_if_over(++spin, 1 << 21);
    }
#pragma unroll
    for (int hi = 0; hi < 2; hi++) {
      const cplx mu = co[hi].mu, mu2 = cmul(mu, mu), mu4 = cmul(mu2, mu2);
      cplx a = cfma(mu4, e[hi][3], e[hi][2]);
      a = cfma(mu4, a, e[hi][1]);
      a = cfma(mu4, a, e[hi][0]);
      if (q & 1) a = cmul(a, mu);
      if (q & 2) a = cmul(a, mu2);
      a.r += __shfl_xor_sync(0xffffffffu, a.r, 1); a.i += __shfl_xor_sync(0xffffffffu, a.i, 1);
      a.r += __shfl_xor_sync(0xffffffffu, a.r, 2); a.i += __shfl_xor_sync(0xffffffffu, a.i, 2);
      if (q & 1) a = cmul(a, co[hi].l32);
      if (q & 2) a = cmul(a, cmul(co[hi].l32, co[hi].l32));
      init[hi].r += a.r; init[hi].i += a.i;
    }
  }
  unsigned char* tile = g_h + (size_t)((rb * NCG + cg) * 2) * CH;
#pragma unroll
  for (int i8 = 0; i8 < 4; i8++) {
    uint32_t pr[2][4], pi[2][4];
#pragma unroll
    for (int jj = 0; jj < 4; jj++) {
#pragma unroll
      for (int hi = 0; hi < 2; hi++) {
        float hr[2], hn[2];
#pragma unroll
        for (int e = 0; e < 2; e++) {
          const int i = 4 * (4 * i8 + jj) + 2 * hi + e;
          init[hi] = cfma(co[hi].lam, init[hi], cplx{vr[i], vi[i]});
          hr[e] = co[hi].c.r * init[hi].r - co[hi].c.i * init[hi].i;
          hn[e] = -co[hi].c.r * init[hi].i - co[hi].c.i * init[hi].r;
        }
        pr[hi][jj] = pack_bf16(hr[0], hr[1]);
        pi[hi][jj] = pack_bf16(hn[0], hn[1]);
      }
    }
#pragma unroll
    for (int hi = 0; hi < 2; hi++) {
      unsigned char* a = tile + (i8 >> 1) * 8192 + (16 * w + 8 * hi + r) * 128 + ((((i8 & 1) * 4 + q) ^ r) << 4);
      st_v4(a, pr[hi][0], pr[hi][1], pr[hi][2], pr[hi][3]);
      st_v4(a + CH, pi[hi][0], pi[hi][1], pi[hi][2], pi[hi][3]);
    }
  }
}

template <bool F>
__device__ __forceinline__ void phase2(const Params& P, uint32_t sb, int rb, int nt, int wg, int w, int lane
) {
  constexpr int NK = F ? NFC : 2 * NCG;
  const int q = lane & 3, r = lane >> 2, warp = wg * 4 + w;
  const int m0 = 64 * wg + 16 * w + r;
  const int mk = m0 + (F ? 8 : 0), ms = m0 + (F ? 0 : 8);
  const int tk = 32 * ((mk >> 3) & 3) + 8 * (mk >> 5) + (mk & 7);
  const int ts = 32 * ((ms >> 3) & 3) + 8 * (ms >> 5) + (ms & 7);
  const int rot = (F && (nt & 1)) ? 2 : 0;
  uint32_t xd[20];
  {
    const __nv_bfloat16* xr = P.xin + (size_t)(rb * 128 + tk) * DM + 160 * nt + 2 * q;
    const __nv_bfloat16* dr = P.dskip + 160 * nt + 2 * q;
#pragma unroll
    for (int j = 0; j < 20; j++) {
      int dj = j + 2 * rot;
      if (dj >= 20) dj -= 20;
      const __nv_bfloat162 a = __ldg((const __nv_bfloat162*)(xr + 8 * dj)), b = __ldg((const __nv_bfloat162*)(dr + 8 * dj));
      const __nv_bfloat162 c = __hmul2(a, b);
      xd[j] = *(const uint32_t*)&c;
    }
  }
  if (lane == 0) mbar_expect_tx(sb + B_RECV + 8 * warp, 5120);
  asm volatile("barrier.cluster.wait.acquire.aligned;" ::: "memory");
  const uint32_t peer = F ? 0 : 1;
  const uint32_t sb16 = (sb & 0x3FFFFu) >> 4;
  float acc[80];
  int s = 0, ph = 0, ps = 0;
  PROF_EV(32 + wg * 8 + 0);
#pragma unroll 1
  for (int k = 0; k < NK; k++) {
    if (threadIdx.x == 128) TR(50 + k, 1);
    { PROF_T0; mbar_wait(sb + B_FULL2 + 8 * s, ph); PROF_ACC(pw); }
    if (threadIdx.x == 128) TR(50 + k, 2);
    const uint32_t a = sb16 + s * (ST2 >> 4) + wg * 512, b = sb16 + s * (ST2 >> 4) + (CH >> 4);
    fence_regs(acc);
    wg_fence();
#pragma unroll
    for (int kk = 0; kk < 4; kk++) {
      const int sc = (k | kk) != 0;
      if (F) wgmma_n160<0, 1>(acc, desc_k(a + kk * 2), desc_mn(b + kk * 128), sc);
      else   wgmma_n160<1, 0>(acc, desc_mn(a + kk * 128), desc_k(b + kk * 2), sc);
    }
    wg_commit();
    if (k > 0) {
      wg_wait<1>();
      if (lane == 0) {
        if (k - 1 < NK - 5) mbar_arrive(sb + B_EMPTY2 + 8 * ps);
        else if (k - 1 == NK - 5) mbar_arrive_remote(mapa(sb + B_PEER, peer));
      }
    }
    fence_regs(acc);
    ps = s;
    if (++s == 5) { s = 0; ph ^= 1; }
  }
  mbar_wait(sb + B_G, 0);
  float gk, gs;
  asm volatile("ld.shared.f32 %0, [%1];" : "=f"(gk) : "r"(sb + SM_G + 4 * tk));
  asm volatile("ld.shared.f32 %0, [%1];" : "=f"(gs) : "r"(sb + SM_G + 4 * ts));
  const float sk = F ? 1.0f - gk : 2.0f * gk, ss = F ? 1.0f - gs : 2.0f * gs;
  mbar_wait_cluster(sb + B_PEER, 0);
  wg_wait<0>();
  fence_regs(acc);
  PROF_EV(32 + wg * 8 + 1);
  constexpr int RSLOT_PEER = F ? (2 * NCG) % 5 : NFC % 5, RSLOT = NK % 5;
  const uint32_t rdst = mapa(sb + RSLOT_PEER * ST2 + warp * 5120 + lane * 16, peer);
  const uint32_t rbar = mapa(sb + B_RECV + 8 * warp, peer);
  constexpr int OS = F ? 0 : 2, OK = F ? 2 : 0;
#pragma unroll
  for (int i = 0; i < 10; i++) {
    int c = i + rot;
    if (c >= 10) c -= 10;
    asm volatile("st.async.weak.shared::cluster.mbarrier::complete_tx::bytes.v4.f32 [%0], {%1, %2, %3, %4}, [%5];"
                 ::"r"(rdst + c * 512), "f"(acc[8 * i + OS] * ss), "f"(acc[8 * i + OS + 1] * ss),
                   "f"(acc[8 * i + 4 + OS] * ss), "f"(acc[8 * i + 4 + OS + 1] * ss), "r"(rbar) : "memory");
  }
  float* orow = P.out + (size_t)(rb * 128 + tk) * DM + 160 * nt + 2 * q;
  mbar_wait_cluster(sb + B_RECV + 8 * warp, 0);
  PROF_EV(32 + wg * 8 + 2);
#pragma unroll
  for (int i = 0; i < 10; i++) {
    int c = i + rot;
    if (c >= 10) c -= 10;
    float4 v;
    asm volatile("ld.shared.v4.f32 {%0, %1, %2, %3}, [%4];" : "=f"(v.x), "=f"(v.y), "=f"(v.z), "=f"(v.w)
                 : "r"(sb + RSLOT * ST2 + warp * 5120 + c * 512 + lane * 16));
    float2 o0, o1;
    o0.x = fmaf(acc[8 * i + OK], sk, fmaf(gk, bf_lo(xd[2 * i]), v.x));
    o0.y = fmaf(acc[8 * i + OK + 1], sk, fmaf(gk, bf_hi(xd[2 * i]), v.y));
    o1.x = fmaf(acc[8 * i + 4 + OK], sk, fmaf(gk, bf_lo(xd[2 * i + 1]), v.z));
    o1.y = fmaf(acc[8 * i + 4 + OK + 1], sk, fmaf(gk, bf_hi(xd[2 * i + 1]), v.w));
    *(float2*)(orow + 16 * c) = o0;
    *(float2*)(orow + 16 * c + 8) = o1;
  }
  PROF_EV(32 + wg * 8 + 3);
}

__global__ void __launch_bounds__(384, 1) __cluster_dims__(2, 1, 1) fused_kernel(const __grid_constant__ Params P) {
  extern __shared__ __align__(1024) unsigned char smem_raw[];
  const uint32_t sb = smem_u32(smem_raw);
  trap_if_over((int)(sb & 1023u), 0);
  const int warp = __shfl_sync(0xffffffffu, threadIdx.x >> 5, 0), lane = threadIdx.x & 31;
  uint32_t ftype, smid;
  asm("mov.u32 %0, %%cluster_ctarank;" : "=r"(ftype));
  asm("mov.u32 %0, %%smid;" : "=r"(smid));
  const int tp = P.use_smid ? (int)(smid >> 1) : (int)(blockIdx.x >> 1);
  int gpc, idx;
  bool extra = false;
  if (tp < 32) { gpc = tp & 7; idx = tp >> 3; }
  else if (tp < 60) { gpc = 1 + (tp - 32) % 7; idx = 4 + (tp - 32) / 7; }
  else if (tp < 62) { gpc = 0; idx = tp - 60; extra = true; }
  else { gpc = 0; idx = tp - 58; }
  const int rb = extra ? (idx * 2 + ftype) * 4 : 2 * gpc + (idx >> 2);
  const int nt = idx & 3;
  const int role = tp * 2 + ftype;
  const int nslots = (extra || ftype) ? 4 : 5;

  if (threadIdx.x == 256) {
    prefetch_map(&P.x); prefetch_map(&P.wg); prefetch_map(&P.wu);
#pragma unroll
    for (int i = 0; i < 38; i++)
      mbar_init(sb + SM_BAR + 8 * i, i < 14 ? 1 : i < 18 ? 4 : i < 23 ? 1 : i < 28 ? 8 : i == 28 ? 64 : i == 29 ? 8 : 1);
    asm volatile("st.shared.u32 [%0], %1;" ::"r"(sb + SM_READY), "r"(0) : "memory");
    asm volatile("fence.mbarrier_init.release.cluster;" ::: "memory");
  }
  __syncthreads();
  asm volatile("barrier.cluster.arrive.relaxed.aligned;" ::: "memory");

  if (warp >= 8) {
    asm volatile("setmaxnreg.dec.sync.aligned.u32 40;");
    if (warp == 8) {
      if (lane == 0) {
        const int n1 = nslots * 10;
        {
          const int fc0 = extra ? EXTRA_FC : ftype * 4 + nt;
          for (int k = 0; k < 10; k++) {
            const uint32_t res = sb + SM_RES + k * CH, ring = sb + SM_RING + k * CH;
            const uint32_t bx = sb + B_XFULL + 8 * k, bf = sb + B_FULL1 + 8 * k;
            mbar_expect_tx(bx, k == 0 ? CH + 1280 : CH);
            if (k < 4) mbar_expect_tx(bf, CH);
            if (!extra) {
              tma5d(res, &P.x, 64 * k, rb, bx);
              if (k < 4) { tma2d(ring, &P.wg, 64 * fc0, 64 * k, bf); tma2d(ring + 8192, &P.wu, 64 * fc0, 64 * k, bf); }
            } else {
              tma2d(res, &P.wg, 64 * fc0, 64 * k, bx); tma2d(res + 8192, &P.wu, 64 * fc0, 64 * k, bx);
              if (k < 4) tma5d(ring, &P.x, 64 * k, rb, bf);
            }
            if (k == 0) bulk_load(sb + SM_GW, P.gatew, 1280, bx);
          }
          prefetch_map(&P.bre); prefetch_map(&P.bim);
          if (ftype) { prefetch_map(&P.wd); prefetch_map(&P.wdw[nt]); } else { prefetch_map(&P.cre); prefetch_map(&P.cim); }
        }
        int slot = 0, k = 4;
        bool ssm = false;
        int id = extra ? 0 : unit_of(ftype, nt, 0, ssm);
        for (int it = 4; it < n1; it++) {
          if (k == 10) { k = 0; slot++; if (!extra) id = unit_of(ftype, nt, slot, ssm); }
          const int s = it & 3;
          const uint32_t ring = sb + SM_RING + s * CH, bf = sb + B_FULL1 + 8 * s;
          { PROF_T0; mbar_wait(sb + B_EMPTY1 + 8 * s, ((it >> 2) & 1) ^ 1); PROF_ACC(pw1); }
          TR(it, 0);
          mbar_expect_tx(bf, CH);
          if (extra) tma5d(ring, &P.x, 64 * k, rb + slot, bf);
          else if (ssm) { tma2d(ring, &P.bre, 64 * k, 64 * id, bf); tma2d(ring + 8192, &P.bim, 64 * k, 64 * id, bf); }
          else { tma2d(ring, &P.wg, 64 * id, 64 * k, bf); tma2d(ring + 8192, &P.wu, 64 * id, 64 * k, bf); }
          k++;
        }
        if (!extra) {
          const int nk = ftype ? NFC : 2 * NCG;
          const int d0 = 160 * nt + ((nt & 1) ? 32 : 0);
          mbar_wait(sb + B_G, 0);
          int s = 0, ph = 1;
          uint32_t ready = 0;
          for (int k2 = 0; k2 < nk; k2++) {
            if (k2 == 2) { mbar_wait(sb + B_EMPTY1 + 8 * ((n1 - 4) & 3), ((n1 - 4) >> 2) & 1); mbar_wait(sb + B_EMPTY1 + 8 * ((n1 - 3) & 3), ((n1 - 3) >> 2) & 1); }
            if (k2 == 3) { mbar_wait(sb + B_EMPTY1 + 8 * ((n1 - 2) & 3), ((n1 - 2) >> 2) & 1); mbar_wait(sb + B_EMPTY1 + 8 * ((n1 - 1) & 3), ((n1 - 1) >> 2) & 1); }
            if (k2 >= 5) { PROF_T0; mbar_wait(sb + B_EMPTY2 + 8 * s, ph); PROF_ACC(pw2); }
            TR(50 + k2, 0);
            const uint32_t st = sb + s * ST2, bf = sb + B_FULL2 + 8 * s;
            const uint32_t need = ftype ? k2 : (k2 >> 1);
            mbar_expect_tx(bf, ftype ? 40960 : 36864);
            if (ftype) {
              tma5d(st + CH, &P.wd, d0, 2 * k2, bf);
              tma5d(st + CH + 8192, &P.wd, d0 + 64, 2 * k2, bf);
              tma5d(st + CH + 16384, &P.wdw[nt], 0, 2 * k2, bf);
            } else {
              tma2d(st + CH, (k2 & 1) ? &P.cim : &P.cre, 64 * (k2 >> 1), 160 * nt, bf);
            }
            if (ready <= need) {
              int spin = 0;
              PROF_T0;
              do {
                asm volatile("ld.acquire.cta.shared.u32 %0, [%1];" : "=r"(ready) : "r"(sb + SM_READY) : "memory");
                trap_if_over(++spin, 1 << 26);
              } while (ready <= need);
              asm volatile("fence.proxy.async.global;" ::: "memory");
              PROF_ACC(pw3);
            }
            bulk_load(st, ftype ? g_act + (size_t)(rb * NFC + k2) * CH : g_h + (size_t)(rb * 2 * NCG + k2) * CH, CH, bf);
            if (++s == 5) { s = 0; ph ^= 1; }
          }
        }
      }
    } else if (warp == 9) {
      const unsigned want = load_epoch(role) + 1;
      if (!extra) {
        mbar_wait(sb + B_XFULL + 8 * 9, 0);
        if (lane == 0) {
          const int pc = (rb * 4 + nt) * 2 + ftype;
          l2_prefetch(P.p_cre + pc * 6400, 6400);
          l2_prefetch(P.p_cim + pc * 6400, 6400);
          l2_prefetch(P.p_wd + pc * 17280, 17280);
        }
      }
      for (int slot = 0; slot < nslots; slot++) {
        bool ssm = false;
        const int id = extra ? EXTRA_FC : unit_of(ftype, nt, slot, ssm);
        bar_sync(3 + ((slot + nslots) & 1), 160);
        if (lane == 0) {
          asm volatile("fence.acq_rel.gpu;" ::: "memory");
          asm volatile("st.relaxed.gpu.global.u32 [%0], %1;" ::"l"((ssm ? g_flag_h : g_flag_act) + (extra ? rb + slot : rb) * 32 + id), "r"(want) : "memory");
        }
        __syncwarp();
      }
    } else if (!extra) {
      const unsigned want = load_epoch(role) + 1;
      const int r0 = (warp - 10) * 64 + lane;
      float a0 = 0.f, a1 = 0.f;
#pragma unroll 1
      for (int k = 0; k < 10; k++) {
        mbar_wait(sb + B_XFULL + 8 * k, 0);
#pragma unroll 2
        for (int c = 0; c < 8; c++) {
          uint4 gw, u, v;
          const uint32_t ad = sb + SM_RES + k * CH + r0 * 128 + ((c ^ (r0 & 7)) << 4);
          asm volatile("ld.shared.v4.u32 {%0, %1, %2, %3}, [%4];" : "=r"(gw.x), "=r"(gw.y), "=r"(gw.z), "=r"(gw.w) : "r"(sb + SM_GW + 128 * k + 16 * c));
          asm volatile("ld.shared.v4.u32 {%0, %1, %2, %3}, [%4];" : "=r"(u.x), "=r"(u.y), "=r"(u.z), "=r"(u.w) : "r"(ad));
          asm volatile("ld.shared.v4.u32 {%0, %1, %2, %3}, [%4];" : "=r"(v.x), "=r"(v.y), "=r"(v.z), "=r"(v.w) : "r"(ad + 32 * 128));
          const uint32_t gg[4] = {gw.x, gw.y, gw.z, gw.w}, uu[4] = {u.x, u.y, u.z, u.w}, vv[4] = {v.x, v.y, v.z, v.w};
#pragma unroll
          for (int i = 0; i < 4; i++) {
            a0 = fmaf(bf_lo(uu[i]), bf_lo(gg[i]), fmaf(bf_hi(uu[i]), bf_hi(gg[i]), a0));
            a1 = fmaf(bf_lo(vv[i]), bf_lo(gg[i]), fmaf(bf_hi(vv[i]), bf_hi(gg[i]), a1));
          }
        }
      }
      const int r1 = r0 + 32;
      const int t0 = 32 * ((r0 >> 1) & 3) + 2 * (r0 >> 3) + (r0 & 1), t1 = 32 * ((r1 >> 1) & 3) + 2 * (r1 >> 3) + (r1 & 1);
      asm volatile("st.shared.f32 [%0], %1;" ::"r"(sb + SM_G + 4 * t0), "f"(1.0f / (1.0f + expf(-a0))) : "memory");
      asm volatile("st.shared.f32 [%0], %1;" ::"r"(sb + SM_G + 4 * t1), "f"(1.0f / (1.0f + expf(-a1))) : "memory");
      mbar_arrive(sb + B_G);
      if (warp == 11) {
        const int nf = ftype ? NFC : NCG;
        const unsigned* fl = (ftype ? g_flag_act : g_flag_h) + rb * 32 + lane;
        uint32_t last = 0;
        int spin = 0;
        while (last < (uint32_t)nf) {
          unsigned v = want;
          if (lane < nf) asm volatile("ld.acquire.gpu.global.u32 %0, [%1];" : "=r"(v) : "l"(fl) : "memory");
          const unsigned miss = __ballot_sync(0xffffffffu, v != want);
          const uint32_t n = miss ? __ffs(miss) - 1 : 32;
          __syncwarp();
          if (n > last) {
            last = n;
            if (lane == 0) asm volatile("st.release.cta.shared.u32 [%0], %1;" ::"r"(sb + SM_READY), "r"(n) : "memory");
          } else {
            __nanosleep(200);
          }
          trap_if_over(++spin, 1 << 22);
        }
      }
    }
    __syncwarp();
    asm volatile("barrier.cluster.wait.acquire.aligned;" ::: "memory");
  } else {
    asm volatile("setmaxnreg.inc.sync.aligned.u32 232;");
    const int wg = warp >> 2, w = warp & 3;
    const unsigned tag = load_epoch(role);
    bool first = true;
#pragma unroll 1
    for (int slot = (wg + nslots) & 1; slot < nslots; slot += 2) {
      bool ssm = false;
      const int id = extra ? EXTRA_FC : unit_of(ftype, nt, slot, ssm);
      const bool signal = slot + 1 < nslots;
      float acc0[64], acc1[64];
      if (ssm) {
        SsmCoef co[2];
        co[0] = ssm_coef(P, 64 * id + 16 * w + (lane >> 2));
        co[1] = ssm_coef(P, 64 * id + 16 * w + (lane >> 2) + 8);
        bar_sync(1 + wg, 256);
        PROF_EV(slot * 4 + 0);
        unit_mainloop<true>(acc0, acc1, sb, slot * 10, first, false, signal, wg, lane PROF_ARGS);
        PROF_EV(slot * 4 + 1);
        ssm_epilogue(acc0, acc1, co, rb, id, tag + 1, w, lane);
        PROF_EV(slot * 4 + 2);
        bar_arrive(3 + wg, 160);
      } else {
        if (slot > 0) bar_sync(1 + wg, 256);
        PROF_EV(slot * 4 + 0);
        unit_mainloop<false>(acc0, acc1, sb, slot * 10, first, extra, signal, wg, lane PROF_ARGS);
        PROF_EV(slot * 4 + 1);
        const int rbo = extra ? rb + slot : rb;
        unsigned char* tile = g_act + (size_t)(rbo * NFC + id) * CH;
        ffn_half(acc0, tile, 0, w, lane);
        ffn_half(acc1, tile, 1, w, lane);
        PROF_EV(slot * 4 + 2);
        bar_arrive(3 + wg, 160);
      }
      PROF_EV(slot * 4 + 3);
      first = false;
    }
    if (extra) {
      asm volatile("barrier.cluster.wait.acquire.aligned;" ::: "memory");
    } else {
      if (ftype) phase2<true>(P, sb, rb, nt, wg, w, lane);
      else phase2<false>(P, sb, rb, nt, wg, w, lane);
    }
    bar_sync(5, 256);
    if (threadIdx.x == 0) g_epoch[role] = tag + 1;
  }
}

typedef CUresult (*EncodeFn)(CUtensorMap*, CUtensorMapDataType, cuuint32_t, void*, const cuuint64_t*, const cuuint64_t*,
                             const cuuint32_t*, const cuuint32_t*, CUtensorMapInterleave, CUtensorMapSwizzle,
                             CUtensorMapL2promotion, CUtensorMapFloatOOBfill);

void encode(EncodeFn fn, CUtensorMap* m, const void* base, int rank, const cuuint64_t* dims, const cuuint64_t* strides,
            const cuuint32_t* box) {
  const cuuint32_t es[5] = {1, 1, 1, 1, 1};
  fn(m, CU_TENSOR_MAP_DATA_TYPE_BFLOAT16, rank, const_cast<void*>(base), dims, strides, box, es,
     CU_TENSOR_MAP_INTERLEAVE_NONE, CU_TENSOR_MAP_SWIZZLE_128B, CU_TENSOR_MAP_L2_PROMOTION_L2_128B,
     CU_TENSOR_MAP_FLOAT_OOB_FILL_NONE);
}

}

extern "C" void kernel_launch(void* const* d_in, const int* in_sizes, int n_in, void* d_out, int out_size) {
  (void)in_sizes; (void)n_in; (void)out_size;
  static EncodeFn enc = nullptr;
  static int sms = 0;
  if (!enc) {
    void* fn = nullptr;
    cudaDriverEntryPointQueryResult qr;
    cudaGetDriverEntryPoint("cuTensorMapEncodeTiled", &fn, cudaEnableDefault, &qr);
    enc = (EncodeFn)fn;
    int dev = 0;
    cudaGetDevice(&dev);
    cudaDeviceGetAttribute(&sms, cudaDevAttrMultiProcessorCount, dev);
    cudaFuncSetAttribute(fused_kernel, cudaFuncAttributeMaxDynamicSharedMemorySize, SMEM_BYTES);
  }
  typedef const __nv_bfloat16* bp;
  Params P;
  const cuuint64_t R = DM * 2;
  {
    const cuuint64_t d[5] = {DM, 2, 4, 16, NRB}, s[4] = {R, 32 * R, 2 * R, 128 * R};
    const cuuint32_t b[5] = {64, 2, 4, 16, 1};
    encode(enc, &P.x, d_in[0], 5, d, s, b);
  }
  {
    const cuuint64_t d[2] = {DM, DM}, s[1] = {R};
    const cuuint32_t b[2] = {64, 64}, bc[2] = {64, 160};
    encode(enc, &P.bre, d_in[3], 2, d, s, b);
    encode(enc, &P.bim, d_in[4], 2, d, s, b);
    encode(enc, &P.cre, d_in[5], 2, d, s, bc);
    encode(enc, &P.cim, d_in[6], 2, d, s, bc);
  }
  {
    const cuuint64_t d[2] = {FF, DM}, s[1] = {FF * 2};
    const cuuint32_t b[2] = {64, 64};
    encode(enc, &P.wg, d_in[10], 2, d, s, b);
    encode(enc, &P.wu, d_in[11], 2, d, s, b);
  }
  {
    cuuint64_t d[5] = {DM, 2, 4, 4, FF / 32};
    const cuuint64_t s[4] = {R, 8 * R, 2 * R, 32 * R};
    const cuuint32_t b[5] = {64, 2, 4, 4, 2};
    encode(enc, &P.wd, d_in[12], 5, d, s, b);
    d[0] = 32;
    for (int nt = 0; nt < 4; nt++) encode(enc, &P.wdw[nt], (bp)d_in[12] + 160 * nt + ((nt & 1) ? 0 : 128), 5, d, s, b);
  }
  P.xin = (bp)d_in[0]; P.lre = (bp)d_in[1]; P.lim = (bp)d_in[2]; P.logdt = (bp)d_in[7]; P.dskip = (bp)d_in[8];
  P.gatew = (bp)d_in[13];
  P.p_bre = (const char*)d_in[3]; P.p_bim = (const char*)d_in[4]; P.p_cre = (const char*)d_in[5]; P.p_cim = (const char*)d_in[6];
  P.p_wg = (const char*)d_in[10]; P.p_wu = (const char*)d_in[11]; P.p_wd = (const char*)d_in[12];
  P.out = (float*)d_out;
  P.use_smid = sms == 132;
  fused_kernel<<<132, 384, SMEM_BYTES, cudaStreamPerThread>>>(P);
}
```

```cpp
#include <cuda_runtime.h>
#include <cuda_bf16.h>
#include <cuda.h>
#include <stdint.h>

#define RELH 0
#define PF0 4
#define PFD 2400
#define P1DENSE 0
#define NCH 3
#define GATHER_AT 40
#define PMCH 1
#define P2DENSE 1
#define STAG 1
#define XSK 4
namespace {

constexpr int DM = 640, FF = 1728;
constexpr int NRB = 16;
constexpr int NFC = 27;
constexpr int NCG = 10;
constexpr int CH = 16384;
constexpr int EXTRA_FC = 22;

constexpr int SM_RES = 0;
constexpr int SM_RING = 10 * CH;
constexpr int ST2 = 40960;
constexpr int SM_XS = 5 * ST2;
constexpr int SM_BAR = 14 * CH;
constexpr int B_XFULL = SM_BAR;
constexpr int B_FULL1 = B_XFULL + 80;
constexpr int B_EMPTY1 = B_FULL1 + 32;
constexpr int B_FULL2 = B_EMPTY1 + 32;
constexpr int B_EMPTY2 = B_FULL2 + 40;
constexpr int B_G = B_EMPTY2 + 40;
constexpr int B_PEER = B_G + 8;
constexpr int B_RECV = B_PEER + 8;
constexpr int B_XS = B_RECV + 64;
constexpr int B_COEF = B_XS + 8;
constexpr int SM_READY = B_COEF + 8;
constexpr int SM_G = SM_BAR + 512;
constexpr int SM_GW = SM_BAR + 1024;
constexpr int SMEM_BYTES = SM_GW + 2048;

struct Params {
  CUtensorMap x, bre, bim, wg, wu, cre, cim, wd, xs;
  const __nv_bfloat16 *xin, *lre, *lim, *logdt, *dskip, *gatew;
  const char *p_cre, *p_cim, *p_wd, *p_wg, *p_wu, *p_bre, *p_bim;
  float* out;
  int use_smid;
  uint32_t zero;
};

__device__ __align__(1024) unsigned char g_act[NRB * NFC * CH];
__device__ __align__(1024) unsigned char g_h[NRB * NCG * 2 * CH];
__device__ __align__(16) unsigned long long g_agg[NCG * NRB * 64 * 2];
__device__ unsigned g_flag_act[NRB * 32];
__device__ unsigned g_flag_h[NRB * 32];
__device__ unsigned g_epoch[132];
__device__ __align__(16) float g_gate[2048];
#define PROF_EV(i)
#define TR(it, f)
#define PROF_ARGS
#define PROF_T0
#define PROF_ACC(v)

__device__ __forceinline__ uint32_t smem_u32(const void* p) { return (uint32_t)__cvta_generic_to_shared(p); }
__device__ __forceinline__ bool elect_one() {
  uint32_t p;
  asm volatile("{\n.reg .pred p;\nelect.sync _|p, 0xffffffff;\nselp.u32 %0, 1, 0, p;\n}" : "=r"(p));
  return p != 0;
}
__device__ __forceinline__ void mbar_init(uint32_t bar, uint32_t cnt) {
  asm volatile("mbarrier.init.shared::cta.b64 [%0], %1;" ::"r"(bar), "r"(cnt) : "memory");
}
__device__ __forceinline__ void mbar_expect_tx(uint32_t bar, uint32_t bytes) {
  asm volatile("mbarrier.arrive.expect_tx.shared::cta.b64 _, [%0], %1;" ::"r"(bar), "r"(bytes) : "memory");
}
__device__ __forceinline__ void mbar_arrive(uint32_t bar) {
  asm volatile("mbarrier.arrive.shared::cta.b64 _, [%0];" ::"r"(bar) : "memory");
}
__device__ __forceinline__ uint32_t mapa(uint32_t addr, uint32_t cta) {
  uint32_t r;
  asm("mapa.shared::cluster.u32 %0, %1, %2;" : "=r"(r) : "r"(addr), "r"(cta));
  return r;
}
__device__ __forceinline__ void mbar_arrive_remote(uint32_t cluster_bar) {
  asm volatile("mbarrier.arrive.relaxed.cluster.shared::cluster.b64 _, [%0];" ::"r"(cluster_bar) : "memory");
}
__device__ __forceinline__ void mbar_wait(uint32_t bar, uint32_t parity) {
  asm volatile("{\n.reg .pred p;\n.reg .u32 c;\nmov.u32 c, 0;\n"
               "W:\nmbarrier.try_wait.parity.shared::cta.b64 p, [%0], %1;\n@p bra D;\n"
               "add.u32 c, c, 1;\nsetp.gt.u32 p, c, 1048576;\n@p trap;\nbra W;\nD:\n}"
               ::"r"(bar), "r"(parity) : "memory");
}
__device__ __forceinline__ void mbar_wait_cluster(uint32_t bar, uint32_t parity) {
  asm volatile("{\n.reg .pred p;\n.reg .u32 c;\nmov.u32 c, 0;\n"
               "W:\nmbarrier.try_wait.parity.acquire.cluster.shared::cta.b64 p, [%0], %1;\n@p bra D;\n"
               "add.u32 c, c, 1;\nsetp.gt.u32 p, c, 1048576;\n@p trap;\nbra W;\nD:\n}"
               ::"r"(bar), "r"(parity) : "memory");
}
__device__ __forceinline__ uint32_t mbar_test(uint32_t bar, uint32_t parity) {
  uint32_t ok;
  asm volatile("{\n.reg .pred p;\nmbarrier.test_wait.parity.shared::cta.b64 p, [%1], %2;\nselp.u32 %0, 1, 0, p;\n}"
               : "=r"(ok) : "r"(bar), "r"(parity) : "memory");
  return ok;
}
__device__ __forceinline__ void mbar_arrive_elect(uint32_t bar) {
  asm volatile("{\n.reg .pred p;\nelect.sync _|p, 0xffffffff;\n@p mbarrier.arrive.shared::cta.b64 _, [%0];\n}" ::"r"(bar) : "memory");
}
__device__ __forceinline__ void trap_if_over(int n, int limit) {
  asm volatile("{\n.reg .pred p;\nsetp.gt.s32 p, %0, %1;\n@p trap;\n}" ::"r"(n), "r"(limit));
}
__device__ __forceinline__ void bulk_load(uint32_t dst, const void* src, uint32_t bytes, uint32_t bar) {
  asm volatile("cp.async.bulk.shared::cluster.global.mbarrier::complete_tx::bytes [%0], [%1], %2, [%3];"
               ::"r"(dst), "l"(src), "r"(bytes), "r"(bar) : "memory");
}
__device__ __forceinline__ void tma2d(uint32_t dst, const CUtensorMap* m, int c0, int c1, uint32_t bar) {
  asm volatile("cp.async.bulk.tensor.2d.shared::cluster.global.mbarrier::complete_tx::bytes [%0], [%1, {%3, %4}], [%2];"
               ::"r"(dst), "l"(m), "r"(bar), "r"(c0), "r"(c1) : "memory");
}
__device__ __forceinline__ void tma5d(uint32_t dst, const CUtensorMap* m, int c0, int c4, uint32_t bar) {
  asm volatile("cp.async.bulk.tensor.5d.shared::cluster.global.mbarrier::complete_tx::bytes [%0], [%1, {%3, %5, %5, %5, %4}], [%2];"
               ::"r"(dst), "l"(m), "r"(bar), "r"(c0), "r"(c4), "r"(0) : "memory");
}
__device__ __forceinline__ void l2_prefetch(const void* p, uint32_t bytes) {
  asm volatile("cp.async.bulk.prefetch.L2.global [%0], %1;" ::"l"(p), "r"(bytes) : "memory");
}
__device__ __forceinline__ void prefetch_map(const CUtensorMap* m) {
  asm volatile("prefetch.tensormap [%0];" ::"l"(m) : "memory");
}
__device__ __forceinline__ void wg_fence() { asm volatile("wgmma.fence.sync.aligned;" ::: "memory"); }
__device__ __forceinline__ void wg_commit() { asm volatile("wgmma.commit_group.sync.aligned;" ::: "memory"); }
template <int N> __device__ __forceinline__ void wg_wait() { asm volatile("wgmma.wait_group.sync.aligned %0;" ::"n"(N) : "memory"); }
template <int R> __device__ __forceinline__ void fence_regs(float (&d)[R]) {
#pragma unroll
  for (int i = 0; i < R; i++) asm volatile("" : "+f"(d[i])::"memory");
}
__device__ __forceinline__ uint64_t desc_k(uint32_t a16) { return ((uint64_t)0x40000040u << 32) | (uint64_t)(a16 + (1u << 16)); }
__device__ __forceinline__ uint64_t desc_mn(uint32_t a16) { return ((uint64_t)0x40000040u << 32) | (uint64_t)(a16 + (512u << 16)); }
__device__ __forceinline__ void bar_sync(int id, int n) { asm volatile("bar.sync %0, %1;" ::"r"(id), "r"(n) : "memory"); }
__device__ __forceinline__ void bar_arrive(int id, int n) { asm volatile("bar.arrive %0, %1;" ::"r"(id), "r"(n) : "memory"); }
__device__ __forceinline__ uint32_t pack_bf16(float lo, float hi) {
  uint32_t r;
  asm("cvt.rn.bf16x2.f32 %0, %1, %2;" : "=r"(r) : "f"(hi), "f"(lo));
  return r;
}
__device__ __forceinline__ float bf_lo(uint32_t v) { return __uint_as_float(v << 16); }
__device__ __forceinline__ float bf_hi(uint32_t v) { return __uint_as_float(v & 0xFFFF0000u); }
__device__ __forceinline__ void st_v4(void* p, uint32_t a, uint32_t b, uint32_t c, uint32_t d) {
  asm volatile("st.global.v4.b32 [%0], {%1, %2, %3, %4};" ::"l"(p), "r"(a), "r"(b), "r"(c), "r"(d) : "memory");
}
__device__ __forceinline__ float fast_ex2(float x) { float y; asm("ex2.approx.ftz.f32 %0, %1;" : "=f"(y) : "f"(x)); return y; }
__device__ __forceinline__ float fast_rcp(float x) { float y; asm("rcp.approx.ftz.f32 %0, %1;" : "=f"(y) : "f"(x)); return y; }
struct cplx { float r, i; };
__device__ __forceinline__ cplx cmul(cplx a, cplx b) { return {a.r * b.r - a.i * b.i, a.r * b.i + a.i * b.r}; }
__device__ __forceinline__ cplx cfma(cplx a, cplx b, cplx c) {
  return {fmaf(a.r, b.r, fmaf(-a.i, b.i, c.r)), fmaf(a.r, b.i, fmaf(a.i, b.r, c.i))};
}
__device__ __forceinline__ cplx cshfl_up(cplx a, int d) {
  return {__shfl_up_sync(0xffffffffu, a.r, d, 4), __shfl_up_sync(0xffffffffu, a.i, d, 4)};
}

template <int TA, int TB>
__device__ __forceinline__ void wgmma_n8(float (&d)[4], uint64_t da, uint64_t db, int scale_d) {
  asm volatile("{\n.reg .pred p;\nsetp.ne.b32 p, %6, 0;\n"
    "wgmma.mma_async.sync.aligned.m64n8k16.f32.bf16.bf16 {"
    "%0, %1, %2, %3"
    "}, %4, %5, p, 1, 1, %7, %8;\n}\n"
    : "+f"(d[0]), "+f"(d[1]), "+f"(d[2]), "+f"(d[3])
    : "l"(da), "l"(db), "r"(scale_d), "n"(TA), "n"(TB));
}
template <int TA, int TB>
__device__ __forceinline__ void wgmma_n8_z(float (&d)[4], uint64_t da, uint64_t db) {
  asm volatile("{\n.reg .pred p;\nsetp.ne.b32 p, 0, 0;\n"
    "wgmma.mma_async.sync.aligned.m64n8k16.f32.bf16.bf16 {"
    "%0, %1, %2, %3"
    "}, %4, %5, p, 1, 1, %6, %7;\n}\n"
    : "=f"(d[0]), "=f"(d[1]), "=f"(d[2]), "=f"(d[3])
    : "l"(da), "l"(db), "n"(TA), "n"(TB));
}

template <int TA, int TB>
__device__ __forceinline__ void wgmma_n64(float (&d)[32], uint64_t da, uint64_t db, int scale_d) {
  asm volatile("{\n.reg .pred p;\nsetp.ne.b32 p, %34, 0;\n"
    "wgmma.mma_async.sync.aligned.m64n64k16.f32.bf16.bf16 {"
    "%0, %1, %2, %3, %4, %5, %6, %7, %8, %9, %10, %11, %12, %13, %14, %15, "
    "%16, %17, %18, %19, %20, %21, %22, %23, %24, %25, %26, %27, %28, %29, %30, %31"
    "}, %32, %33, p, 1, 1, %35, %36;\n}\n"
    : "+f"(d[0]), "+f"(d[1]), "+f"(d[2]), "+f"(d[3]), "+f"(d[4]), "+f"(d[5]), "+f"(d[6]), "+f"(d[7]),
      "+f"(d[8]), "+f"(d[9]), "+f"(d[10]), "+f"(d[11]), "+f"(d[12]), "+f"(d[13]), "+f"(d[14]), "+f"(d[15]),
      "+f"(d[16]), "+f"(d[17]), "+f"(d[18]), "+f"(d[19]), "+f"(d[20]), "+f"(d[21]), "+f"(d[22]), "+f"(d[23]),
      "+f"(d[24]), "+f"(d[25]), "+f"(d[26]), "+f"(d[27]), "+f"(d[28]), "+f"(d[29]), "+f"(d[30]), "+f"(d[31])
    : "l"(da), "l"(db), "r"(scale_d), "n"(TA), "n"(TB));
}
template <int TA, int TB>
__device__ __forceinline__ void wgmma_n64_z(float (&d)[32], uint64_t da, uint64_t db) {
  asm volatile("{\n.reg .pred p;\nsetp.ne.b32 p, 0, 0;\n"
    "wgmma.mma_async.sync.aligned.m64n64k16.f32.bf16.bf16 {"
    "%0, %1, %2, %3, %4, %5, %6, %7, %8, %9, %10, %11, %12, %13, %14, %15, "
    "%16, %17, %18, %19, %20, %21, %22, %23, %24, %25, %26, %27, %28, %29, %30, %31"
    "}, %32, %33, p, 1, 1, %34, %35;\n}\n"
    : "=f"(d[0]), "=f"(d[1]), "=f"(d[2]), "=f"(d[3]), "=f"(d[4]), "=f"(d[5]), "=f"(d[6]), "=f"(d[7]),
      "=f"(d[8]), "=f"(d[9]), "=f"(d[10]), "=f"(d[11]), "=f"(d[12]), "=f"(d[13]), "=f"(d[14]), "=f"(d[15]),
      "=f"(d[16]), "=f"(d[17]), "=f"(d[18]), "=f"(d[19]), "=f"(d[20]), "=f"(d[21]), "=f"(d[22]), "=f"(d[23]),
      "=f"(d[24]), "=f"(d[25]), "=f"(d[26]), "=f"(d[27]), "=f"(d[28]), "=f"(d[29]), "=f"(d[30]), "=f"(d[31])
    : "l"(da), "l"(db), "n"(TA), "n"(TB));
}

template <int TA, int TB>
__device__ __forceinline__ void wgmma_n96(float (&d)[48], uint64_t da, uint64_t db, int scale_d) {
  asm volatile("{\n.reg .pred p;\nsetp.ne.b32 p, %50, 0;\n"
    "wgmma.mma_async.sync.aligned.m64n96k16.f32.bf16.bf16 {"
    "%0, %1, %2, %3, %4, %5, %6, %7, %8, %9, %10, %11, %12, %13, %14, %15, "
    "%16, %17, %18, %19, %20, %21, %22, %23, %24, %25, %26, %27, %28, %29, %30, %31, "
    "%32, %33, %34, %35, %36, %37, %38, %39, %40, %41, %42, %43, %44, %45, %46, %47"
    "}, %48, %49, p, 1, 1, %51, %52;\n}\n"
    : "+f"(d[0]), "+f"(d[1]), "+f"(d[2]), "+f"(d[3]), "+f"(d[4]), "+f"(d[5]), "+f"(d[6]), "+f"(d[7]),
      "+f"(d[8]), "+f"(d[9]), "+f"(d[10]), "+f"(d[11]), "+f"(d[12]), "+f"(d[13]), "+f"(d[14]), "+f"(d[15]),
      "+f"(d[16]), "+f"(d[17]), "+f"(d[18]), "+f"(d[19]), "+f"(d[20]), "+f"(d[21]), "+f"(d[22]), "+f"(d[23]),
      "+f"(d[24]), "+f"(d[25]), "+f"(d[26]), "+f"(d[27]), "+f"(d[28]), "+f"(d[29]), "+f"(d[30]), "+f"(d[31]),
      "+f"(d[32]), "+f"(d[33]), "+f"(d[34]), "+f"(d[35]), "+f"(d[36]), "+f"(d[37]), "+f"(d[38]), "+f"(d[39]),
      "+f"(d[40]), "+f"(d[41]), "+f"(d[42]), "+f"(d[43]), "+f"(d[44]), "+f"(d[45]), "+f"(d[46]), "+f"(d[47])
    : "l"(da), "l"(db), "r"(scale_d), "n"(TA), "n"(TB));
}
template <int TA, int TB>
__device__ __forceinline__ void wgmma_n96_z(float (&d)[48], uint64_t da, uint64_t db) {
  asm volatile("{\n.reg .pred p;\nsetp.ne.b32 p, 0, 0;\n"
    "wgmma.mma_async.sync.aligned.m64n96k16.f32.bf16.bf16 {"
    "%0, %1, %2, %3, %4, %5, %6, %7, %8, %9, %10, %11, %12, %13, %14, %15, "
    "%16, %17, %18, %19, %20, %21, %22, %23, %24, %25, %26, %27, %28, %29, %30, %31, "
    "%32, %33, %34, %35, %36, %37, %38, %39, %40, %41, %42, %43, %44, %45, %46, %47"
    "}, %48, %49, p, 1, 1, %50, %51;\n}\n"
    : "=f"(d[0]), "=f"(d[1]), "=f"(d[2]), "=f"(d[3]), "=f"(d[4]), "=f"(d[5]), "=f"(d[6]), "=f"(d[7]),
      "=f"(d[8]), "=f"(d[9]), "=f"(d[10]), "=f"(d[11]), "=f"(d[12]), "=f"(d[13]), "=f"(d[14]), "=f"(d[15]),
      "=f"(d[16]), "=f"(d[17]), "=f"(d[18]), "=f"(d[19]), "=f"(d[20]), "=f"(d[21]), "=f"(d[22]), "=f"(d[23]),
      "=f"(d[24]), "=f"(d[25]), "=f"(d[26]), "=f"(d[27]), "=f"(d[28]), "=f"(d[29]), "=f"(d[30]), "=f"(d[31]),
      "=f"(d[32]), "=f"(d[33]), "=f"(d[34]), "=f"(d[35]), "=f"(d[36]), "=f"(d[37]), "=f"(d[38]), "=f"(d[39]),
      "=f"(d[40]), "=f"(d[41]), "=f"(d[42]), "=f"(d[43]), "=f"(d[44]), "=f"(d[45]), "=f"(d[46]), "=f"(d[47])
    : "l"(da), "l"(db), "n"(TA), "n"(TB));
}

template <int TA, int TB>
__device__ __forceinline__ void wgmma_n128(float (&d)[64], uint64_t da, uint64_t db, int scale_d) {
  asm volatile("{\n.reg .pred p;\nsetp.ne.b32 p, %66, 0;\n"
    "wgmma.mma_async.sync.aligned.m64n128k16.f32.bf16.bf16 {"
    "%0, %1, %2, %3, %4, %5, %6, %7, %8, %9, %10, %11, %12, %13, %14, %15, "
    "%16, %17, %18, %19, %20, %21, %22, %23, %24, %25, %26, %27, %28, %29, %30, %31, "
    "%32, %33, %34, %35, %36, %37, %38, %39, %40, %41, %42, %43, %44, %45, %46, %47, "
    "%48, %49, %50, %51, %52, %53, %54, %55, %56, %57, %58, %59, %60, %61, %62, %63"
    "}, %64, %65, p, 1, 1, %67, %68;\n}\n"
    : "+f"(d[0]), "+f"(d[1]), "+f"(d[2]), "+f"(d[3]), "+f"(d[4]), "+f"(d[5]), "+f"(d[6]), "+f"(d[7]),
      "+f"(d[8]), "+f"(d[9]), "+f"(d[10]), "+f"(d[11]), "+f"(d[12]), "+f"(d[13]), "+f"(d[14]), "+f"(d[15]),
      "+f"(d[16]), "+f"(d[17]), "+f"(d[18]), "+f"(d[19]), "+f"(d[20]), "+f"(d[21]), "+f"(d[22]), "+f"(d[23]),
      "+f"(d[24]), "+f"(d[25]), "+f"(d[26]), "+f"(d[27]), "+f"(d[28]), "+f"(d[29]), "+f"(d[30]), "+f"(d[31]),
      "+f"(d[32]), "+f"(d[33]), "+f"(d[34]), "+f"(d[35]), "+f"(d[36]), "+f"(d[37]), "+f"(d[38]), "+f"(d[39]),
      "+f"(d[40]), "+f"(d[41]), "+f"(d[42]), "+f"(d[43]), "+f"(d[44]), "+f"(d[45]), "+f"(d[46]), "+f"(d[47]),
      "+f"(d[48]), "+f"(d[49]), "+f"(d[50]), "+f"(d[51]), "+f"(d[52]), "+f"(d[53]), "+f"(d[54]), "+f"(d[55]),
      "+f"(d[56]), "+f"(d[57]), "+f"(d[58]), "+f"(d[59]), "+f"(d[60]), "+f"(d[61]), "+f"(d[62]), "+f"(d[63])
    : "l"(da), "l"(db), "r"(scale_d), "n"(TA), "n"(TB));
}
template <int TA, int TB>
__device__ __forceinline__ void wgmma_n128_z(float (&d)[64], uint64_t da, uint64_t db) {
  asm volatile("{\n.reg .pred p;\nsetp.ne.b32 p, 0, 0;\n"
    "wgmma.mma_async.sync.aligned.m64n128k16.f32.bf16.bf16 {"
    "%0, %1, %2, %3, %4, %5, %6, %7, %8, %9, %10, %11, %12, %13, %14, %15, "
    "%16, %17, %18, %19, %20, %21, %22, %23, %24, %25, %26, %27, %28, %29, %30, %31, "
    "%32, %33, %34, %35, %36, %37, %38, %39, %40, %41, %42, %43, %44, %45, %46, %47, "
    "%48, %49, %50, %51, %52, %53, %54, %55, %56, %57, %58, %59, %60, %61, %62, %63"
    "}, %64, %65, p, 1, 1, %66, %67;\n}\n"
    : "=f"(d[0]), "=f"(d[1]), "=f"(d[2]), "=f"(d[3]), "=f"(d[4]), "=f"(d[5]), "=f"(d[6]), "=f"(d[7]),
      "=f"(d[8]), "=f"(d[9]), "=f"(d[10]), "=f"(d[11]), "=f"(d[12]), "=f"(d[13]), "=f"(d[14]), "=f"(d[15]),
      "=f"(d[16]), "=f"(d[17]), "=f"(d[18]), "=f"(d[19]), "=f"(d[20]), "=f"(d[21]), "=f"(d[22]), "=f"(d[23]),
      "=f"(d[24]), "=f"(d[25]), "=f"(d[26]), "=f"(d[27]), "=f"(d[28]), "=f"(d[29]), "=f"(d[30]), "=f"(d[31]),
      "=f"(d[32]), "=f"(d[33]), "=f"(d[34]), "=f"(d[35]), "=f"(d[36]), "=f"(d[37]), "=f"(d[38]), "=f"(d[39]),
      "=f"(d[40]), "=f"(d[41]), "=f"(d[42]), "=f"(d[43]), "=f"(d[44]), "=f"(d[45]), "=f"(d[46]), "=f"(d[47]),
      "=f"(d[48]), "=f"(d[49]), "=f"(d[50]), "=f"(d[51]), "=f"(d[52]), "=f"(d[53]), "=f"(d[54]), "=f"(d[55]),
      "=f"(d[56]), "=f"(d[57]), "=f"(d[58]), "=f"(d[59]), "=f"(d[60]), "=f"(d[61]), "=f"(d[62]), "=f"(d[63])
    : "l"(da), "l"(db), "n"(TA), "n"(TB));
}

template <int TA, int TB>
__device__ __forceinline__ void wgmma_n160(float (&d)[80], uint64_t da, uint64_t db, int scale_d) {
  asm volatile("{\n.reg .pred p;\nsetp.ne.b32 p, %82, 0;\n"
    "wgmma.mma_async.sync.aligned.m64n160k16.f32.bf16.bf16 {"
    "%0, %1, %2, %3, %4, %5, %6, %7, %8, %9, %10, %11, %12, %13, %14, %15, "
    "%16, %17, %18, %19, %20, %21, %22, %23, %24, %25, %26, %27, %28, %29, %30, %31, "
    "%32, %33, %34, %35, %36, %37, %38, %39, %40, %41, %42, %43, %44, %45, %46, %47, "
    "%48, %49, %50, %51, %52, %53, %54, %55, %56, %57, %58, %59, %60, %61, %62, %63, "
    "%64, %65, %66, %67, %68, %69, %70, %71, %72, %73, %74, %75, %76, %77, %78, %79"
    "}, %80, %81, p, 1, 1, %83, %84;\n}\n"
    : "+f"(d[0]), "+f"(d[1]), "+f"(d[2]), "+f"(d[3]), "+f"(d[4]), "+f"(d[5]), "+f"(d[6]), "+f"(d[7]),
      "+f"(d[8]), "+f"(d[9]), "+f"(d[10]), "+f"(d[11]), "+f"(d[12]), "+f"(d[13]), "+f"(d[14]), "+f"(d[15]),
      "+f"(d[16]), "+f"(d[17]), "+f"(d[18]), "+f"(d[19]), "+f"(d[20]), "+f"(d[21]), "+f"(d[22]), "+f"(d[23]),
      "+f"(d[24]), "+f"(d[25]), "+f"(d[26]), "+f"(d[27]), "+f"(d[28]), "+f"(d[29]), "+f"(d[30]), "+f"(d[31]),
      "+f"(d[32]), "+f"(d[33]), "+f"(d[34]), "+f"(d[35]), "+f"(d[36]), "+f"(d[37]), "+f"(d[38]), "+f"(d[39]),
      "+f"(d[40]), "+f"(d[41]), "+f"(d[42]), "+f"(d[43]), "+f"(d[44]), "+f"(d[45]), "+f"(d[46]), "+f"(d[47]),
      "+f"(d[48]), "+f"(d[49]), "+f"(d[50]), "+f"(d[51]), "+f"(d[52]), "+f"(d[53]), "+f"(d[54]), "+f"(d[55]),
      "+f"(d[56]), "+f"(d[57]), "+f"(d[58]), "+f"(d[59]), "+f"(d[60]), "+f"(d[61]), "+f"(d[62]), "+f"(d[63]),
      "+f"(d[64]), "+f"(d[65]), "+f"(d[66]), "+f"(d[67]), "+f"(d[68]), "+f"(d[69]), "+f"(d[70]), "+f"(d[71]),
      "+f"(d[72]), "+f"(d[73]), "+f"(d[74]), "+f"(d[75]), "+f"(d[76]), "+f"(d[77]), "+f"(d[78]), "+f"(d[79])
    : "l"(da), "l"(db), "r"(scale_d), "n"(TA), "n"(TB));
}
template <int TA, int TB>
__device__ __forceinline__ void wgmma_n160_z(float (&d)[80], uint64_t da, uint64_t db) {
  asm volatile("{\n.reg .pred p;\nsetp.ne.b32 p, 0, 0;\n"
    "wgmma.mma_async.sync.aligned.m64n160k16.f32.bf16.bf16 {"
    "%0, %1, %2, %3, %4, %5, %6, %7, %8, %9, %10, %11, %12, %13, %14, %15, "
    "%16, %17, %18, %19, %20, %21, %22, %23, %24, %25, %26, %27, %28, %29, %30, %31, "
    "%32, %33, %34, %35, %36, %37, %38, %39, %40, %41, %42, %43, %44, %45, %46, %47, "
    "%48, %49, %50, %51, %52, %53, %54, %55, %56, %57, %58, %59, %60, %61, %62, %63, "
    "%64, %65, %66, %67, %68, %69, %70, %71, %72, %73, %74, %75, %76, %77, %78, %79"
    "}, %80, %81, p, 1, 1, %82, %83;\n}\n"
    : "=f"(d[0]), "=f"(d[1]), "=f"(d[2]), "=f"(d[3]), "=f"(d[4]), "=f"(d[5]), "=f"(d[6]), "=f"(d[7]),
      "=f"(d[8]), "=f"(d[9]), "=f"(d[10]), "=f"(d[11]), "=f"(d[12]), "=f"(d[13]), "=f"(d[14]), "=f"(d[15]),
      "=f"(d[16]), "=f"(d[17]), "=f"(d[18]), "=f"(d[19]), "=f"(d[20]), "=f"(d[21]), "=f"(d[22]), "=f"(d[23]),
      "=f"(d[24]), "=f"(d[25]), "=f"(d[26]), "=f"(d[27]), "=f"(d[28]), "=f"(d[29]), "=f"(d[30]), "=f"(d[31]),
      "=f"(d[32]), "=f"(d[33]), "=f"(d[34]), "=f"(d[35]), "=f"(d[36]), "=f"(d[37]), "=f"(d[38]), "=f"(d[39]),
      "=f"(d[40]), "=f"(d[41]), "=f"(d[42]), "=f"(d[43]), "=f"(d[44]), "=f"(d[45]), "=f"(d[46]), "=f"(d[47]),
      "=f"(d[48]), "=f"(d[49]), "=f"(d[50]), "=f"(d[51]), "=f"(d[52]), "=f"(d[53]), "=f"(d[54]), "=f"(d[55]),
      "=f"(d[56]), "=f"(d[57]), "=f"(d[58]), "=f"(d[59]), "=f"(d[60]), "=f"(d[61]), "=f"(d[62]), "=f"(d[63]),
      "=f"(d[64]), "=f"(d[65]), "=f"(d[66]), "=f"(d[67]), "=f"(d[68]), "=f"(d[69]), "=f"(d[70]), "=f"(d[71]),
      "=f"(d[72]), "=f"(d[73]), "=f"(d[74]), "=f"(d[75]), "=f"(d[76]), "=f"(d[77]), "=f"(d[78]), "=f"(d[79])
    : "l"(da), "l"(db), "n"(TA), "n"(TB));
}

__device__ __forceinline__ unsigned load_epoch(int role) {
  unsigned tag;
  asm volatile("ld.relaxed.gpu.global.u32 %0, [%1];" : "=r"(tag) : "l"(g_epoch + role) : "memory");
  return tag;
}

__device__ __forceinline__ int unit_of(int ftype, int nt, int s, bool& ssm) {
  const int c = ftype * 4 + nt;
  ssm = false;
  if (s == 0) return c;
  if (s == 1) { ssm = true; return c; }
  if (s == 2) {
    if (!ftype) return 10 + nt;
    ssm = nt < 2;
    return ssm ? 8 + nt : 6 + nt;
  }
  if (s == 3) return 14 + c;
  return 23 + nt;
}

template <int MODE, bool ZERO>
__device__ __forceinline__ void unit_mma(float (&acc0)[64], float (&acc1)[64], float (&g0)[4], float (&g1)[4], uint32_t xa,
                                         uint32_t wa, uint32_t ga, int kk) {
  if (MODE == 1) {
    const uint64_t db = desc_k(xa + kk * 2);
    if (ZERO) { wgmma_n128_z<0, 0>(acc0, desc_k(wa), db); wgmma_n128_z<0, 0>(acc1, desc_k(wa + 512), db); }
    else { wgmma_n128<0, 0>(acc0, desc_k(wa + kk * 2), db, 1); wgmma_n128<0, 0>(acc1, desc_k(wa + 512 + kk * 2), db, 1); }
  } else {
    const uint64_t db = desc_mn(wa + kk * 128);
    if (ZERO) { wgmma_n128_z<0, 1>(acc0, desc_k(xa), db); wgmma_n128_z<0, 1>(acc1, desc_k(xa + 512), db); }
    else { wgmma_n128<0, 1>(acc0, desc_k(xa + kk * 2), db, 1); wgmma_n128<0, 1>(acc1, desc_k(xa + 512 + kk * 2), db, 1); }
    if (MODE == 2) {
      const uint64_t dg = ((uint64_t)1 << 32) | (uint64_t)(ga + kk * 2 + (1u << 16));
      if (ZERO) { wgmma_n8_z<0, 0>(g0, desc_k(xa), dg); wgmma_n8_z<0, 0>(g1, desc_k(xa + 512), dg); }
      else { wgmma_n8<0, 0>(g0, desc_k(xa + kk * 2), dg, 1); wgmma_n8<0, 0>(g1, desc_k(xa + 512 + kk * 2), dg, 1); }
    }
  }
}
template <int MODE>
__device__ __forceinline__ void unit_fence(float (&acc0)[64], float (&acc1)[64], float (&g0)[4], float (&g1)[4]) {
  fence_regs(acc0); fence_regs(acc1);
  if (MODE == 2) { fence_regs(g0); fence_regs(g1); }
}
template <int MODE, bool K0>
__device__ __forceinline__ uint32_t unit_kstep(float (&acc0)[64], float (&acc1)[64], float (&g0)[4], float (&g1)[4], uint32_t sb,
                                               int k, uint32_t& s, uint32_t& ph, bool first) {
  const uint32_t sb16 = (sb & 0x3FFFFu) >> 4;
  const uint32_t res = sb16 + (SM_RES >> 4) + k * (CH >> 4), ring = sb16 + (SM_RING >> 4) + s * (CH >> 4);
  const uint32_t xa = MODE == 2 ? ring : res, wa = MODE == 2 ? res : ring, ga = sb16 + (SM_GW >> 4) + k * 8;
  const uint32_t sp = (s + 3) & 3;
  s = (s + 1) & 3;
  ph ^= (s == 0);
  if (!K0) unit_fence<MODE>(acc0, acc1, g0, g1);
  wg_fence();
  unit_mma<MODE, K0>(acc0, acc1, g0, g1, xa, wa, ga, 0);
  unit_mma<MODE, false>(acc0, acc1, g0, g1, xa, wa, ga, 1);
  wg_commit();
  if (!K0) {
    wg_wait<1>();
    mbar_arrive_elect(sb + B_EMPTY1 + 8 * sp);
  }
  uint32_t ok = mbar_test(sb + B_FULL1 + 8 * s, ph);
  if (first) ok &= mbar_test(sb + B_XFULL + 8 * (k + 1), 0);
  unit_fence<MODE>(acc0, acc1, g0, g1);
  wg_fence();
  unit_mma<MODE, false>(acc0, acc1, g0, g1, xa, wa, ga, 2);
  unit_mma<MODE, false>(acc0, acc1, g0, g1, xa, wa, ga, 3);
  wg_commit();
  unit_fence<MODE>(acc0, acc1, g0, g1);
  return ok;
}
template <int MODE>
__device__ __forceinline__ void unit_mainloop(float (&acc0)[64], float (&acc1)[64], float (&g0)[4], float (&g1)[4], uint32_t sb,
                                              int it0, bool first, bool signal, int wg, int lane
) {
  uint32_t s = it0 & 3, ph = (it0 >> 2) & 1;
  if (first) mbar_wait(sb + B_XFULL, 0);
  mbar_wait(sb + B_FULL1 + 8 * s, ph);
  if ((threadIdx.x & 127) == 0) TR(it0, 2);
  uint32_t ok = unit_kstep<MODE, true>(acc0, acc1, g0, g1, sb, 0, s, ph, first);
#pragma unroll 1
  for (int k = 1; k < 10; k++) {
    if ((threadIdx.x & 127) == 0) TR(it0 + k, 1);
    if (!ok) {
      if (first) mbar_wait(sb + B_XFULL + 8 * k, 0);
      mbar_wait(sb + B_FULL1 + 8 * s, ph);
    }
    if ((threadIdx.x & 127) == 0) TR(it0 + k, 2);
    ok = unit_kstep<MODE, false>(acc0, acc1, g0, g1, sb, k, s, ph, first);
  }
  if (signal) bar_arrive(1 + (wg ^ 1), 256);
  wg_wait<0>();
  unit_fence<MODE>(acc0, acc1, g0, g1);
  mbar_arrive_elect(sb + B_EMPTY1 + 8 * ((s + 3) & 3));
}

__device__ __forceinline__ float chain(float x, float y, uint32_t zero) {
  return __uint_as_float(__float_as_uint(x) | (__float_as_uint(y) & zero));
}

template <bool PACED, int mh>
__device__ __forceinline__ void ffn_half(const float (&a)[64], unsigned char* tile, int w, int lane, float (&v)[NCH],
                                         uint32_t zero) {
  const int q = lane & 3, r = lane >> 2;
#pragma unroll
  for (int hi = 0; hi < 2; hi++) {
    const int m7 = 4 * (w & 1) + 2 * hi + (r & 1);
    const int m = (2 * mh + (w >> 1)) * 32 + (r >> 1) * 8 + m7;
    unsigned char* row = tile + m * 128;
#pragma unroll
    for (int h = 0; h < 2; h++) {
      uint32_t p[4];
#pragma unroll
      for (int j = 0; j < 4; j++) {
        float o[2];
#pragma unroll
        for (int e = 0; e < 2; e++) {
          const int i = 4 * (4 * h + j) + 2 * hi + e, c = (32 * mh + 16 * hi + 8 * h + 2 * j + e) % NCH;
          const float sg = fast_rcp(1.0f + fast_ex2(a[i] * (PACED ? chain(-1.4426950408889634f, v[c], zero) : -1.4426950408889634f)));
          v[c] = o[e] = (a[i] * sg) * a[32 + i];
        }
        p[j] = pack_bf16(o[0], o[1]);
      }
      st_v4(row + (((4 * h + q) ^ m7) << 4), p[0], p[1], p[2], p[3]);
    }
  }
}

struct SsmCoef { cplx lam, c, l32, l64, mu; };
__device__ __forceinline__ float4 ssm_coef(const Params& P, int p) {
  const float lr = __bfloat162float(P.lre[p]), li = __bfloat162float(P.lim[p]);
  const float dt = __bfloat162float(__float2bfloat16_rn(expf(__bfloat162float(P.logdt[p]))));
  float sn, cs;
  sincosf(dt * li, &sn, &cs);
  const float ex = expf(dt * lr);
  const float nr = ex * cs - 1.0f, ni = ex * sn, den = 1.0f / (lr * lr + li * li);
  return make_float4(ex * cs, ex * sn, (nr * lr + ni * li) * den, (ni * lr - nr * li) * den);
}
__device__ __forceinline__ SsmCoef ssm_powers(uint32_t addr) {
  SsmCoef o;
  asm volatile("ld.shared.v4.f32 {%0, %1, %2, %3}, [%4];" : "=f"(o.lam.r), "=f"(o.lam.i), "=f"(o.c.r), "=f"(o.c.i) : "r"(addr) : "memory");
  cplx t = o.lam;
#pragma unroll
  for (int i = 0; i < 5; i++) t = cmul(t, t);
  o.l32 = t;
  o.l64 = cmul(t, t);
  o.mu = cmul(o.l64, o.l64);
  return o;
}

__device__ __forceinline__ void agg_load(unsigned long long& a, unsigned long long& b, const void* p, int valid) {
  asm volatile("{\n.reg .pred p;\nsetp.ne.s32 p, %3, 0;\n@p ld.relaxed.gpu.global.v2.b64 {%0, %1}, [%2];\n}"
               : "+l"(a), "+l"(b) : "l"(p), "r"(valid) : "memory");
}

__device__ __forceinline__ void ssm_epilogue(const float (&vr)[64], const float (&vi)[64], const SsmCoef (&co)[2], int rb,
                                             int cg, unsigned tag, int w, int lane, uint32_t zero
) {
  const int q = lane & 3, r = lane >> 2;
  char* agg = (char*)g_agg + ((cg * NRB + rb) * 64 + 16 * w + r) * 16;
  float prev = 0.f;
  cplx s1[2];
#pragma unroll
  for (int hi = 0; hi < 2; hi++) {
    const cplx lam = P1DENSE ? co[hi].lam : cplx{chain(co[hi].lam.r, prev, zero), chain(co[hi].lam.i, prev, zero)};
    cplx s = {vr[2 * hi], vi[2 * hi]};
#pragma unroll
    for (int t = 1; t < 32; t++) {
      const int i = 4 * (t >> 1) + 2 * hi + (t & 1);
      s = cfma(lam, s, cplx{vr[i], vi[i]});
    }
    s1[hi] = s;
    prev = s.r;
  }
#pragma unroll
  for (int hi = 0; hi < 2; hi++) {
    const cplx y = cshfl_up(s1[hi], 1);
    if (q >= 1) s1[hi] = cfma(co[hi].l32, y, s1[hi]);
  }
#pragma unroll
  for (int hi = 0; hi < 2; hi++) {
    const cplx y = cshfl_up(s1[hi], 2);
    if (q >= 2) s1[hi] = cfma(co[hi].l64, y, s1[hi]);
    const unsigned long long a = ((unsigned long long)tag << 32) | __float_as_uint(s1[hi].r);
    const unsigned long long b = ((unsigned long long)tag << 32) | __float_as_uint(s1[hi].i);
    asm volatile("{\n.reg .pred p;\nsetp.eq.s32 p, %3, 3;\n@p st.relaxed.gpu.global.v2.b64 [%0], {%1, %2};\n}"
                 ::"l"(agg + 128 * hi), "l"(a), "l"(b), "r"(q) : "memory");
  }
  PROF_EV(20 + slot * 2);
  cplx h0[2], mq[2], m4[2], lq[2];
#pragma unroll
  for (int hi = 0; hi < 2; hi++) {
    const cplx y = cshfl_up(s1[hi], 1), one = {1.f, 0.f};
    h0[hi] = q >= 1 ? cmul(co[hi].c, y) : cplx{0.f, 0.f};
    prev = y.i;
    const cplx mu2 = cmul(co[hi].mu, co[hi].mu);
    m4[hi] = cmul(mu2, mu2);
    mq[hi] = cmul((q & 1) ? co[hi].mu : one, (q & 2) ? mu2 : one);
    lq[hi] = cmul(cmul((q & 1) ? co[hi].l32 : one, (q & 2) ? co[hi].l64 : one), co[hi].c);
  }
  const int nv = rb - q;
  const char* src = agg - (1 + q) * 1024;
  unsigned long long ea[2][4], eb[2][4];
  float wr[64], wn[64];
#pragma unroll
  for (int t = 0; t < 64; t++) {
    if (t == GATHER_AT) {
      const char* sp = src + (__float_as_uint(prev) & zero);
#pragma unroll
      for (int m = 0; m < 4; m++)
#pragma unroll
        for (int h2 = 0; h2 < 2; h2++) {
          asm volatile("{\n.reg .pred p;\nsetp.ne.s32 p, %3, 0;\n@p ld.relaxed.gpu.global.v2.b64 {%0, %1}, [%2];\n}"
                       : "=l"(ea[h2][m]), "=l"(eb[h2][m]) : "l"(sp + 128 * h2 - 4096 * m), "r"((int)(4 * m < nv)) : "memory");
        }
    }
    const int hi = t >> 5, i = 4 * ((t & 31) >> 1) + 2 * hi + (t & 1);
    const float cr = t % PMCH == 0 ? chain(co[hi].c.r, prev, zero) : prev, ci = co[hi].c.i, a = vr[i], b = vi[i];
    wr[i] = fmaf(-ci, b, cr * a);
    wn[i] = fmaf(-ci, a, -cr * b);
    prev = (t + 1) % PMCH == 0 ? wr[i] : cr;
  }
  int spin = 0;
  while (true) {
    bool ok = true;
#pragma unroll
    for (int m = 0; m < 4; m++) {
      const unsigned x = ((unsigned)(ea[0][m] >> 32) ^ tag) | ((unsigned)(eb[0][m] >> 32) ^ tag) |
                         ((unsigned)(ea[1][m] >> 32) ^ tag) | ((unsigned)(eb[1][m] >> 32) ^ tag);
      ok = ok && (x == 0 || 4 * m >= nv);
    }
    if (__all_sync(0xffffffffu, ok)) break;
#pragma unroll
    for (int m = 0; m < 4; m++)
#pragma unroll
      for (int hi = 0; hi < 2; hi++) agg_load(ea[hi][m], eb[hi][m], src + 128 * hi - 4096 * m, 4 * m < nv);
    trap_if_over(++spin, 1 << 21);
  }
  PROF_EV(21 + slot * 2);
#pragma unroll
  for (int hi = 0; hi < 2; hi++) {
    cplx a = {0.f, 0.f};
#pragma unroll
    for (int m = 3; m >= 0; m--)
      if (4 * m < nv) a = cfma(m4[hi], a, cplx{__uint_as_float((unsigned)ea[hi][m]), __uint_as_float((unsigned)eb[hi][m])});
    a = cmul(a, mq[hi]);
    a.r += __shfl_xor_sync(0xffffffffu, a.r, 1); a.i += __shfl_xor_sync(0xffffffffu, a.i, 1);
    a.r += __shfl_xor_sync(0xffffffffu, a.r, 2); a.i += __shfl_xor_sync(0xffffffffu, a.i, 2);
    h0[hi] = cfma(lq[hi], a, h0[hi]);
  }
  unsigned char* tile = g_h + (size_t)((rb * NCG + cg) * 2) * CH + (16 * w + r) * 128;
  unsigned char* t0 = tile + ((q ^ r) << 4);
  unsigned char* t1 = tile + (((4 + q) ^ r) << 4);
  prev = h0[1].i;
#pragma unroll
  for (int hi = 0; hi < 2; hi++) {
    const cplx lam = co[hi].lam;
    float hr = P2DENSE ? h0[hi].r : chain(h0[hi].r, prev, zero), hn = P2DENSE ? -h0[hi].i : chain(-h0[hi].i, prev, zero);
#pragma unroll
    for (int i8 = 0; i8 < 4; i8++) {
      uint32_t pr[4], pi[4];
#pragma unroll
      for (int jj = 0; jj < 4; jj++) {
        float fr[2], fn[2];
#pragma unroll
        for (int e = 0; e < 2; e++) {
          const int i = 4 * (4 * i8 + jj) + 2 * hi + e;
          const float nr = fmaf(lam.r, hr, fmaf(lam.i, hn, wr[i]));
          const float nn = fmaf(lam.r, hn, fmaf(-lam.i, hr, wn[i]));
          fr[e] = hr = nr; fn[e] = hn = nn;
        }
        pr[jj] = pack_bf16(fr[0], fr[1]);
        pi[jj] = pack_bf16(fn[0], fn[1]);
      }
      unsigned char* a = ((i8 & 1) ? t1 : t0) + (i8 >> 1) * 8192 + hi * 1024;
      st_v4(a, pr[0], pr[1], pr[2], pr[3]);
      st_v4(a + CH, pi[0], pi[1], pi[2], pi[3]);
    }
    prev = hr;
  }
}

__device__ __forceinline__ void ldmatrix4(uint32_t* r, uint32_t addr) {
  asm volatile("ldmatrix.sync.aligned.m8n8.x4.shared.b16 {%0, %1, %2, %3}, [%4];"
               : "=r"(r[0]), "=r"(r[1]), "=r"(r[2]), "=r"(r[3]) : "r"(addr) : "memory");
}

template <bool F, bool K0, int NA>
__device__ __forceinline__ void p2_mma(float (&acc)[NA], float (&acb)[32], uint32_t a, uint32_t b, uint32_t lbo96) {
  if (!K0) { fence_regs(acc); if (F) fence_regs(acb); }
  wg_fence();
#pragma unroll
  for (int kk = 0; kk < 4; kk++) {
    if constexpr (F) {
      const uint64_t d96 = ((uint64_t)0x40000040u << 32) | (uint64_t)(b + kk * 128 + lbo96);
      if (K0 && kk == 0) { wgmma_n96_z<0, 1>(acc, desc_k(a), d96); wgmma_n64_z<0, 1>(acb, desc_k(a), desc_mn(b + 512)); }
      else { wgmma_n96<0, 1>(acc, desc_k(a + kk * 2), d96, 1); wgmma_n64<0, 1>(acb, desc_k(a + kk * 2), desc_mn(b + 512 + kk * 128), 1); }
    } else {
      if (K0 && kk == 0) wgmma_n160_z<1, 0>(acc, desc_mn(a), desc_k(b));
      else wgmma_n160<1, 0>(acc, desc_mn(a + kk * 128), desc_k(b + kk * 2), 1);
    }
  }
  wg_commit();
  fence_regs(acc);
  if (F) fence_regs(acb);
}

template <bool F>
__device__ __forceinline__ void phase2(const Params& P, uint32_t sb, int rb, int nt, int wg, int w, int lane
) {
  constexpr int NK = F ? NFC : 2 * NCG;
  const int q = lane & 3, r = lane >> 2, warp = wg * 4 + w;
  if (elect_one()) mbar_expect_tx(sb + B_RECV + 8 * warp, 2560);
  asm volatile("barrier.cluster.wait.acquire.aligned;" ::: "memory");
  const uint32_t peer = F ? 0 : 1;
  const uint32_t sb16 = (sb & 0x3FFFFu) >> 4;
  float acc[F ? 48 : 80], acb[32];
  const int rot = (F && (nt & 1)) ? 1 : 0;
  const uint32_t lbo96 = (1024u + 4u * rot) << 16;
#define ACC(i) (F && (i) >= 48 ? acb[(i) >= 48 ? (i) - 48 : 0] : acc[F && (i) >= 48 ? 0 : (i)])
  PROF_EV(32 + wg * 8 + 0);
  mbar_wait(sb + B_FULL2, 0);
  p2_mma<F, true>(acc, acb, sb16 + wg * 512, sb16 + (CH >> 4), lbo96);
  int s = 1, ph = 0;
#pragma unroll 1
  for (int k = 1; k < NK; k++) {
    if (k == NK - 4 && wg == 1) {
      wg_wait<0>();
      if (elect_one()) mbar_arrive_remote(mapa(sb + B_PEER, peer));
      if (STAG) bar_sync(6, 256);
    }
    if (threadIdx.x == 128) TR(50 + k, 1);
    { PROF_T0; mbar_wait(sb + B_FULL2 + 8 * s, ph); PROF_ACC(pw); }
    if (threadIdx.x == 128) TR(50 + k, 2);
    p2_mma<F, false>(acc, acb, sb16 + s * (ST2 >> 4) + wg * 512, sb16 + s * (ST2 >> 4) + (CH >> 4), lbo96);
    wg_wait<1>();
    if (k < NK - 4) mbar_arrive_elect(sb + B_EMPTY2 + 8 * (s == 0 ? 4 : s - 1));
    else if (k == NK - 4 && wg == 0 && elect_one()) mbar_arrive_remote(mapa(sb + B_PEER, peer));
    if (++s == 5) { s = 0; ph ^= 1; }
  }
  if (STAG && wg == 0) bar_arrive(6, 256);
  const int lrow = 8 * (2 * wg + (w >> 1));
  const int tk = 64 * (w & 1) + (F ? 32 : 0) + lrow + r;
#define CB(n) (!F ? (n) : (n) < 2 ? (n) + rot : (n) == 2 ? 4 - 4 * rot : (n) - 1 + rot)
  constexpr int RSLOT = NK % 5, RSLOT_PEER = F ? (2 * NCG) % 5 : NFC % 5;
  float g;
  uint32_t xd[20];
  mbar_wait(sb + B_G, 0);
  asm volatile("ld.shared.f32 %0, [%1];" : "=f"(g) : "r"(sb + SM_G + 4 * tk) : "memory");
  mbar_wait(sb + B_XS, 0);
  {
    const uint32_t xa = sb + SM_XS + (w & 1) * 10752 + (lrow + (lane & 7)) * 336 + (lane >> 3) * 16;
    const uint32_t da = sb + SM_XS + 21504 + (lane >> 3) * 16;
#pragma unroll
    for (int n = 0; n < 5; n++) {
      uint32_t xv[4], dv[4];
      ldmatrix4(xv, xa + CB(n) * 64);
      ldmatrix4(dv, da + CB(n) * 64);
#pragma unroll
      for (int i = 0; i < 4; i++) asm("mul.bf16x2 %0, %1, %2;" : "=r"(xd[4 * n + i]) : "r"(xv[i]), "r"(dv[i]));
    }
  }
  const uint32_t rdst = mapa(sb + RSLOT_PEER * ST2 + warp * 2560 + lane * 16, peer);
  const uint32_t rbar = mapa(sb + B_RECV + 8 * warp, peer);
  const bool odd = q & 1;
  const uint32_t rsrc = sb + RSLOT * ST2 + warp * 2560 + (lane & ~1) * 16 + (odd ? 8 : 0);
  float* orow = P.out + (size_t)(rb * 128 + tk) * DM + 160 * nt + (odd ? 2 * q + 6 : 2 * q);
  const float sk = F ? 1.0f - g : 2.0f * g, sr = F ? 2.0f * g : 1.0f - g;
  constexpr int OS = F ? 0 : 2, OK = F ? 2 : 0;
  mbar_wait_cluster(sb + B_PEER, 0);
  wg_wait<0>();
  fence_regs(acc);
  if (F) fence_regs(acb);
  PROF_EV(32 + wg * 8 + 1);
#pragma unroll
  for (int n = 0; n < 5; n++) {
    uint32_t p[4];
#pragma unroll
    for (int i = 0; i < 4; i++) p[i] = pack_bf16(ACC(16 * n + 4 * i + OS), ACC(16 * n + 4 * i + OS + 1));
    asm volatile("st.async.weak.shared::cluster.mbarrier::complete_tx::bytes.v4.b32 [%0], {%1, %2, %3, %4}, [%5];"
                 ::"r"(rdst + CB(n) * 512), "r"(p[0]), "r"(p[2]), "r"(p[1]), "r"(p[3]), "r"(rbar) : "memory");
  }
  float o[40];
#pragma unroll
  for (int i = 0; i < 10; i++) {
    float a[2], b[2];
#pragma unroll
    for (int e = 0; e < 2; e++) {
      const float u0 = fmaf(ACC(8 * i + OK + e), sk, g * (e ? bf_hi(xd[2 * i]) : bf_lo(xd[2 * i])));
      const float u1 = fmaf(ACC(8 * i + 4 + OK + e), sk, g * (e ? bf_hi(xd[2 * i + 1]) : bf_lo(xd[2 * i + 1])));
      a[e] = odd ? u1 : u0;
      b[e] = __shfl_xor_sync(0xffffffffu, odd ? u0 : u1, 1);
    }
    o[4 * i] = odd ? b[0] : a[0]; o[4 * i + 1] = odd ? b[1] : a[1];
    o[4 * i + 2] = odd ? a[0] : b[0]; o[4 * i + 3] = odd ? a[1] : b[1];
  }
  fence_regs(o);
  mbar_wait_cluster(sb + B_RECV + 8 * warp, 0);
  PROF_EV(32 + wg * 8 + 2);
#pragma unroll
  for (int n = 0; n < 5; n++) {
    uint32_t lo[2], hi[2];
    asm volatile("ld.shared.v2.b32 {%0, %1}, [%2];" : "=r"(lo[0]), "=r"(lo[1]) : "r"(rsrc + CB(n) * 512) : "memory");
    asm volatile("ld.shared.v2.b32 {%0, %1}, [%2];" : "=r"(hi[0]), "=r"(hi[1]) : "r"(rsrc + CB(n) * 512 + 16) : "memory");
#pragma unroll
    for (int h = 0; h < 2; h++) {
      const int i = 2 * n + h;
      *(float4*)(orow + 32 * CB(n) + 16 * h) = make_float4(fmaf(bf_lo(lo[h]), sr, o[4 * i]), fmaf(bf_hi(lo[h]), sr, o[4 * i + 1]),
                                                           fmaf(bf_lo(hi[h]), sr, o[4 * i + 2]), fmaf(bf_hi(hi[h]), sr, o[4 * i + 3]));
    }
  }
  PROF_EV(32 + wg * 8 + 3);
#undef ACC
#undef CB
}

__global__ void __launch_bounds__(384, 1) __cluster_dims__(2, 1, 1) fused_kernel(const __grid_constant__ Params P) {
  extern __shared__ __align__(1024) unsigned char smem_raw[];
  const uint32_t sb = smem_u32(smem_raw);
  trap_if_over((int)(sb & 1023u), 0);
  const int warp = __shfl_sync(0xffffffffu, threadIdx.x >> 5, 0), lane = threadIdx.x & 31;
  if (warp == 10 && elect_one()) { prefetch_map(&P.x); prefetch_map(&P.wg); prefetch_map(&P.wu); }
  uint32_t ftype, smid;
  asm("mov.u32 %0, %%cluster_ctarank;" : "=r"(ftype));
  asm("mov.u32 %0, %%smid;" : "=r"(smid));
  const int tp = P.use_smid ? (int)(smid >> 1) : (int)(blockIdx.x >> 1);
  int gpc, idx;
  bool extra = false;
  if (tp < 32) { gpc = tp & 7; idx = tp >> 3; }
  else if (tp < 60) { gpc = 1 + (tp - 32) % 7; idx = 4 + (tp - 32) / 7; }
  else if (tp < 62) { gpc = 0; idx = tp - 60; extra = true; }
  else { gpc = 0; idx = tp - 58; }
  const int rb = extra ? (idx * 2 + ftype) * 4 : 2 * gpc + (idx >> 2);
  const int nt = idx & 3;
  const int role = tp * 2 + ftype;
  const int nslots = (extra || ftype) ? 4 : 5;

  if (warp == 8) {
    if (elect_one()) {
#pragma unroll
      for (int i = 0; i < 18; i++) mbar_init(sb + SM_BAR + 8 * i, i < 14 ? 1 : 4);
      asm volatile("fence.mbarrier_init.release.cluster;" ::: "memory");
    }
    __syncwarp();
    bar_arrive(0, 384);
    const int fc0 = extra ? EXTRA_FC : ftype * 4 + nt;
#pragma unroll 1
    for (int k = 0; k < 4; k++) {
      const uint32_t res = sb + SM_RES + k * CH, ring = sb + SM_RING + k * CH;
      const uint32_t bx = sb + B_XFULL + 8 * k, bf = sb + B_FULL1 + 8 * k;
      if (elect_one()) {
        mbar_expect_tx(bx, extra && k == 0 ? CH + 1280 : CH);
        mbar_expect_tx(bf, CH);
        tma5d(extra ? ring : res, &P.x, 64 * k, rb, extra ? bf : bx);
        tma2d(extra ? res : ring, &P.wg, 64 * fc0, 64 * k, extra ? bx : bf);
        tma2d((extra ? res : ring) + 8192, &P.wu, 64 * fc0, 64 * k, extra ? bx : bf);
        if (extra && k == 0) bulk_load(sb + SM_GW, P.gatew, 1280, bx);
      }
    }
  } else {
    if (warp == 9 && elect_one()) {
#pragma unroll
      for (int i = 18; i < 40; i++) mbar_init(sb + SM_BAR + 8 * i, i < 23 ? 1 : i < 28 ? 8 : i == 28 ? 32 : i == 29 ? 8 : i == 39 ? 128 : 1);
      asm volatile("st.shared.u32 [%0], %1;" ::"r"(sb + SM_READY), "r"(0) : "memory");
      asm volatile("fence.mbarrier_init.release.cluster;" ::: "memory");
    }
    __syncwarp();
    bar_sync(0, 384);
  }
  asm volatile("barrier.cluster.arrive.relaxed.aligned;" ::: "memory");

  if (warp >= 8) {
    asm volatile("setmaxnreg.dec.sync.aligned.u32 40;");
    if (warp == 8) {
      int it = 4;
#pragma unroll 1
      for (int slot = 0; slot < nslots; slot++) {
        bool ssm = false;
        const int id = extra ? 0 : unit_of(ftype, nt, slot, ssm);
        const CUtensorMap* m0 = ssm ? &P.bre : &P.wg;
        const int c0 = ssm ? 0 : 64 * id, c1 = ssm ? 64 * id : 0, d0 = ssm ? 64 : 0;
#pragma unroll 1
        for (int k = slot == 0 ? 4 : 0; k < 10; k++, it++) {
          const int s = it & 3;
          const uint32_t ring = sb + SM_RING + s * CH, bf = sb + B_FULL1 + 8 * s;
          if (slot == 0 && elect_one()) {
            const uint32_t res = sb + SM_RES + k * CH, bx = sb + B_XFULL + 8 * k;
            mbar_expect_tx(bx, CH);
            if (!extra) tma5d(res, &P.x, 64 * k, rb, bx);
            else { tma2d(res, &P.wg, 64 * EXTRA_FC, 64 * k, bx); tma2d(res + 8192, &P.wu, 64 * EXTRA_FC, 64 * k, bx); }
          }
          { PROF_T0; mbar_wait(sb + B_EMPTY1 + 8 * s, ((it >> 2) & 1) ^ 1); PROF_ACC(pw1); }
          TR(it, 0);
          if (elect_one()) {
            mbar_expect_tx(bf, CH);
            if (extra) tma5d(ring, &P.x, 64 * k, rb + slot, bf);
            else {
              tma2d(ring, m0, c0 + d0 * k, c1 + (64 - d0) * k, bf);
              tma2d(ring + 8192, m0 + 1, c0 + d0 * k, c1 + (64 - d0) * k, bf);
            }
          }
        }
      }
      if (!extra) {
        const int nk = ftype ? NFC : 2 * NCG;
        const int dc = 160 * nt + ((nt & 1) ? 32 : 0);
        const unsigned char* asrc = ftype ? g_act + (size_t)(rb * NFC) * CH : g_h + (size_t)(rb * 2 * NCG) * CH;
        int s = 0, ph = 1;
        uint32_t ready = 0;
#pragma unroll 1
        for (int k2 = 0; k2 < nk; k2++) {
          if (k2 >= 5) {
            PROF_T0; mbar_wait(sb + B_EMPTY2 + 8 * s, ph); PROF_ACC(pw2);
          } else if (k2 == 2 || k2 == 3) {
            mbar_wait(sb + B_EMPTY1 + 8 * (it & 3), ((it >> 2) & 1) ^ 1);
            it++;
            mbar_wait(sb + B_EMPTY1 + 8 * (it & 3), ((it >> 2) & 1) ^ 1);
            it++;
          }
          TR(50 + k2, 0);
          const uint32_t st = sb + s * ST2, bf = sb + B_FULL2 + 8 * s;
          if (elect_one()) {
            if (ftype) {
              mbar_expect_tx(bf, 40960);
              tma5d(st + CH, &P.wd, dc, 2 * k2, bf);
              tma5d(st + CH + 8192, &P.wd, dc + 64, 2 * k2, bf);
              tma5d(st + CH + 16384, &P.wd, 128 + 320 * (nt >> 1), 2 * k2, bf);
            } else {
              mbar_expect_tx(bf, 36864);
              tma2d(st + CH, &P.cre + (k2 & 1), 64 * (k2 >> 1), 160 * nt, bf);
            }
          }
          const uint32_t need = ftype ? k2 : k2 >> 1;
          if (ready <= need) {
            int spin = 0;
            PROF_T0;
            do {
              asm volatile("ld.acquire.cta.shared.u32 %0, [%1];" : "=r"(ready) : "r"(sb + SM_READY) : "memory");
              trap_if_over(++spin, 1 << 26);
            } while (ready <= need);
            asm volatile("fence.proxy.async.global;" ::: "memory");
            PROF_ACC(pw3);
          }
          if (elect_one()) {
            bulk_load(st, asrc + (size_t)k2 * CH, CH, bf);
            if (k2 == XSK) {
              mbar_expect_tx(sb + B_XS, 21824);
              tma2d(sb + SM_XS, &P.xs, 160 * nt, rb * 128 + 32 * ftype, sb + B_XS);
              tma2d(sb + SM_XS + 10752, &P.xs, 160 * nt, rb * 128 + 64 + 32 * ftype, sb + B_XS);
              bulk_load(sb + SM_XS + 21504, P.dskip + 160 * nt, 320, sb + B_XS);
            }
          }
          if (++s == 5) { s = 0; ph ^= 1; }
        }
      }
    } else if (warp == 9) {
      const unsigned want = load_epoch(role) + 1;
      if (elect_one()) {
        prefetch_map(&P.bre); prefetch_map(&P.bim);
        if (ftype) prefetch_map(&P.wd); else { prefetch_map(&P.cre); prefetch_map(&P.cim); }
        prefetch_map(&P.xs);
      }
      for (int slot = 0; slot < nslots; slot++) {
        bool ssm = false;
        const int id = extra ? EXTRA_FC : unit_of(ftype, nt, slot, ssm);
        bar_sync(3 + ((slot + nslots) & 1), 160);
        if (elect_one()) {
          asm volatile("fence.acq_rel.gpu;" ::: "memory");
          asm volatile("st.relaxed.gpu.global.u32 [%0], %1;" ::"l"((ssm ? g_flag_h : g_flag_act) + (extra ? rb + slot : rb) * 32 + id), "r"(want) : "memory");
        }
        __syncwarp();
      }
      if (extra && lane == 0) asm volatile("red.relaxed.gpu.global.add.u32 [%0], 1;" ::"l"(g_epoch + role) : "memory");
    } else if (warp == 10 && !extra) {
      const unsigned want = load_epoch(role) + 1;
      const int nf = ftype ? NFC : NCG;
      const unsigned* fl = lane == 31 ? g_flag_act + rb * 32 + EXTRA_FC : (ftype ? g_flag_act : g_flag_h) + rb * 32 + lane;
      mbar_wait(sb + B_XFULL + 8 * 9, 0);
      __nanosleep(4000);
      uint32_t last = 0;
      int spin = 0;
      while (last < 32) {
        unsigned v = want;
        if (lane < nf || lane == 31) asm volatile("ld.acquire.gpu.global.u32 %0, [%1];" : "=r"(v) : "l"(fl) : "memory");
        const unsigned miss = __ballot_sync(0xffffffffu, v != want);
        const uint32_t n = miss ? __ffs(miss) - 1 : 32;
        __syncwarp();
        if (n > last) {
          last = n;
          if (lane == 0) asm volatile("st.release.cta.shared.u32 [%0], %1;" ::"r"(sb + SM_READY), "r"(n) : "memory");
        } else {
          __nanosleep(200);
        }
        trap_if_over(++spin, 1 << 22);
      }
      float4 gv;
      asm volatile("ld.relaxed.gpu.global.v4.f32 {%0, %1, %2, %3}, [%4];" : "=f"(gv.x), "=f"(gv.y), "=f"(gv.z), "=f"(gv.w) : "l"(g_gate + rb * 128 + 4 * lane) : "memory");
      asm volatile("st.shared.v4.f32 [%0], {%1, %2, %3, %4};" ::"r"(sb + SM_G + 16 * lane), "f"(gv.x), "f"(gv.y), "f"(gv.z), "f"(gv.w) : "memory");
      mbar_arrive(sb + B_G);
      if (lane == 0) asm volatile("red.relaxed.gpu.global.add.u32 [%0], 1;" ::"l"(g_epoch + role) : "memory");
    } else if (warp == 11 && !extra) {
      const int pc = (rb * 4 + nt) * 2 + ftype;
      const char* wrow = (lane & 1 ? P.p_wu : P.p_wg) + (size_t)(pc * 5 + (lane >> 1)) * (FF * 2);
      mbar_wait(sb + B_XFULL + 8 * PF0, 0);
      if (lane < 2) l2_prefetch((lane ? P.p_bim : P.p_bre) + pc * 5120, 5120);
      mbar_wait(sb + B_XFULL + 8 * 9, 0);
      if (lane < 10) l2_prefetch(wrow + 8 * 128, 6 * 128);
      if (lane < 2) l2_prefetch((lane ? P.p_bim : P.p_bre) + 655360 + pc * 1280, 1280);
      __nanosleep(PFD);
      if (lane < 10) l2_prefetch(wrow + 14 * 128, 8 * 128);
      __nanosleep(PFD / 2);
      if (lane == 0) l2_prefetch(P.p_wd + pc * 8640, 8640);
      __nanosleep(PFD / 2);
      if (lane < 10) l2_prefetch(wrow + 23 * 128, 4 * 128);
      if (lane == 0) l2_prefetch(P.p_wd + 1105920 + pc * 8640, 8640);
      __nanosleep(PFD / 2);
      if (lane < 2) l2_prefetch((lane ? P.p_cim : P.p_cre) + pc * 6400, 6400);
    }
    __syncwarp();
    asm volatile("barrier.cluster.wait.acquire.aligned;" ::: "memory");
  } else {
    const int wg = warp >> 2, w = warp & 3;
    if (((wg + nslots) & 1) != 0) mbar_wait(sb + B_XFULL, 0);
    asm volatile("setmaxnreg.inc.sync.aligned.u32 232;");
    if (extra) {
#pragma unroll 1
      for (int slot = wg; slot < 4; slot += 2) {
        float acc0[64], acc1[64], g0[4], g1[4];
        if (slot > 0) bar_sync(1 + wg, 256);
        PROF_EV(slot * 4 + 0);
        unit_mainloop<2>(acc0, acc1, g0, g1, sb, slot * 10, slot < 2, slot < 3, wg, lane PROF_ARGS);
        PROF_EV(slot * 4 + 1);
        if ((lane & 3) == 0) {
#pragma unroll
          for (int i = 0; i < 4; i++) {
            const int c = 64 * (i >> 1) + 16 * w + 8 * (i & 1) + (lane >> 2);
            const float z = (i >> 1) ? g1[2 * (i & 1)] : g0[2 * (i & 1)];
            g_gate[(rb + slot) * 128 + 32 * ((c >> 1) & 3) + 2 * (c >> 3) + (c & 1)] = 1.0f / (1.0f + expf(-z));
          }
        }
        unsigned char* tile = g_act + (size_t)((rb + slot) * NFC + EXTRA_FC) * CH;
        float v[NCH] = {};
        ffn_half<true, 0>(acc0, tile, w, lane, v, P.zero);
        ffn_half<true, 1>(acc1, tile, w, lane, v, P.zero);
        PROF_EV(slot * 4 + 2);
        bar_arrive(3 + wg, 160);
      }
      asm volatile("barrier.cluster.wait.acquire.aligned;" ::: "memory");
    } else {
#pragma unroll 1
      for (int slot = (wg + nslots) & 1; slot < nslots; slot += 2) {
        bool ssm = false;
        const int id = unit_of(ftype, nt, slot, ssm);
        const bool signal = slot + 1 < nslots;
        float acc0[64], acc1[64], g0[4], g1[4];
        if (ssm) {
          const unsigned tag = load_epoch(role);
          if (slot == 1) {
            const int t = threadIdx.x & 127;
            const float4 cf = ssm_coef(P, t < 64 ? 64 * id + t : 512 + 64 * (nt & 1) + t - 64);
            asm volatile("st.shared.v4.f32 [%0], {%1, %2, %3, %4};" ::"r"(sb + SM_GW + 16 * t), "f"(cf.x), "f"(cf.y), "f"(cf.z), "f"(cf.w) : "memory");
            mbar_arrive(sb + B_COEF);
          }
          mbar_wait(sb + B_COEF, 0);
          SsmCoef co[2];
          co[0] = ssm_powers(sb + SM_GW + (slot - 1) * 1024 + 16 * (16 * w + (lane >> 2)));
          co[1] = ssm_powers(sb + SM_GW + (slot - 1) * 1024 + 16 * (16 * w + (lane >> 2) + 8));
          bar_sync(1 + wg, 256);
          PROF_EV(slot * 4 + 0);
          unit_mainloop<1>(acc0, acc1, g0, g1, sb, slot * 10, slot < 2, signal, wg, lane PROF_ARGS);
          PROF_EV(slot * 4 + 1);
          ssm_epilogue(acc0, acc1, co, rb, id, tag + 1, w, lane, P.zero);
        } else {
          if (slot > 0) bar_sync(1 + wg, 256);
          PROF_EV(slot * 4 + 0);
          unit_mainloop<0>(acc0, acc1, g0, g1, sb, slot * 10, slot < 2, signal, wg, lane PROF_ARGS);
          PROF_EV(slot * 4 + 1);
          unsigned char* tile = g_act + (size_t)(rb * NFC + id) * CH;
          float v[NCH] = {};
          if (signal) {
            ffn_half<true, 0>(acc0, tile, w, lane, v, P.zero);
            ffn_half<true, 1>(acc1, tile, w, lane, v, P.zero);
          } else {
            ffn_half<false, 0>(acc0, tile, w, lane, v, P.zero);
            ffn_half<false, 1>(acc1, tile, w, lane, v, P.zero);
          }
        }
        PROF_EV(slot * 4 + 2);
        bar_arrive(3 + wg, 160);
      }
      if (ftype) phase2<true>(P, sb, rb, nt, wg, w, lane);
      else phase2<false>(P, sb, rb, nt, wg, w, lane);
    }
  }
}

typedef CUresult (*EncodeFn)(CUtensorMap*, CUtensorMapDataType, cuuint32_t, void*, const cuuint64_t*, const cuuint64_t*,
                             const cuuint32_t*, const cuuint32_t*, CUtensorMapInterleave, CUtensorMapSwizzle,
                             CUtensorMapL2promotion, CUtensorMapFloatOOBfill);

void encode(EncodeFn fn, CUtensorMap* m, const void* base, int rank, const cuuint64_t* dims, const cuuint64_t* strides,
            const cuuint32_t* box, CUtensorMapSwizzle swz = CU_TENSOR_MAP_SWIZZLE_128B) {
  const cuuint32_t es[5] = {1, 1, 1, 1, 1};
  fn(m, CU_TENSOR_MAP_DATA_TYPE_BFLOAT16, rank, const_cast<void*>(base), dims, strides, box, es,
     CU_TENSOR_MAP_INTERLEAVE_NONE, swz, CU_TENSOR_MAP_L2_PROMOTION_L2_128B,
     CU_TENSOR_MAP_FLOAT_OOB_FILL_NONE);
}

}

extern "C" void kernel_launch(void* const* d_in, const int* in_sizes, int n_in, void* d_out, int out_size) {
  (void)in_sizes; (void)n_in; (void)out_size;
  static EncodeFn enc = nullptr;
  static int sms = 0;
  if (!enc) {
    void* fn = nullptr;
    cudaDriverEntryPointQueryResult qr;
    cudaGetDriverEntryPoint("cuTensorMapEncodeTiled", &fn, cudaEnableDefault, &qr);
    enc = (EncodeFn)fn;
    int dev = 0;
    cudaGetDevice(&dev);
    cudaDeviceGetAttribute(&sms, cudaDevAttrMultiProcessorCount, dev);
    cudaFuncSetAttribute(fused_kernel, cudaFuncAttributeMaxDynamicSharedMemorySize, SMEM_BYTES);
  }
  typedef const __nv_bfloat16* bp;
  Params P;
  const cuuint64_t R = DM * 2;
  {
    const cuuint64_t d[5] = {DM, 2, 4, 16, NRB}, s[4] = {R, 32 * R, 2 * R, 128 * R};
    const cuuint32_t b[5] = {64, 2, 4, 16, 1};
    encode(enc, &P.x, d_in[0], 5, d, s, b);
  }
  {
    const cuuint64_t d[2] = {DM, DM}, s[1] = {R};
    const cuuint32_t b[2] = {64, 64}, bc[2] = {64, 160};
    encode(enc, &P.bre, d_in[3], 2, d, s, b);
    encode(enc, &P.bim, d_in[4], 2, d, s, b);
    encode(enc, &P.cre, d_in[5], 2, d, s, bc);
    encode(enc, &P.cim, d_in[6], 2, d, s, bc);
  }
  {
    const cuuint64_t d[2] = {FF, DM}, s[1] = {FF * 2};
    const cuuint32_t b[2] = {64, 64};
    encode(enc, &P.wg, d_in[10], 2, d, s, b);
    encode(enc, &P.wu, d_in[11], 2, d, s, b);
  }
  {
    cuuint64_t d[5] = {DM, 2, 4, 4, FF / 32};
    const cuuint64_t s[4] = {R, 8 * R, 2 * R, 32 * R};
    const cuuint32_t b[5] = {64, 2, 4, 4, 2};
    encode(enc, &P.wd, d_in[12], 5, d, s, b);
  }
  {
    const cuuint64_t d[2] = {DM, 2048}, s[1] = {R};
    const cuuint32_t b[2] = {168, 32};
    encode(enc, &P.xs, d_in[0], 2, d, s, b, CU_TENSOR_MAP_SWIZZLE_NONE);
  }
  P.xin = (bp)d_in[0]; P.lre = (bp)d_in[1]; P.lim = (bp)d_in[2]; P.logdt = (bp)d_in[7]; P.dskip = (bp)d_in[8];
  P.gatew = (bp)d_in[13];
  P.p_bre = (const char*)d_in[3]; P.p_bim = (const char*)d_in[4]; P.p_cre = (const char*)d_in[5]; P.p_cim = (const char*)d_in[6];
  P.p_wg = (const char*)d_in[10]; P.p_wu = (const char*)d_in[11]; P.p_wd = (const char*)d_in[12];
  P.out = (float*)d_out;
  P.use_smid = sms == 132;
  P.zero = 0;
  fused_kernel<<<132, 384, SMEM_BYTES, cudaStreamPerThread>>>(P);
}
```

```cpp
#include <cuda_runtime.h>
#include <cuda_bf16.h>
#include <cuda.h>
#include <stdint.h>

#define RELH 0
#define PF0 9
#define PFD 2400
#define P1DENSE 0
#define NCH 3
#define GATHER_AT 40
#define PMCH 1
#define P2DENSE 1
#define STAG 1
#define XSK 4
#define NPRE 4
#define SF 0
#define MAP 1
namespace {

constexpr int DM = 640, FF = 1728;
constexpr int NRB = 16;
constexpr int NFC = 27;
constexpr int NCG = 10;
constexpr int CH = 16384;
constexpr int EXTRA_FC = 22;

constexpr int SM_RES = 0;
constexpr int SM_RING = 10 * CH;
constexpr int ST2 = 40960;
constexpr int SM_XS = 5 * ST2;
constexpr int SM_BAR = 14 * CH;
constexpr int B_XFULL = SM_BAR;
constexpr int B_FULL1 = B_XFULL + 80;
constexpr int B_EMPTY1 = B_FULL1 + 32;
constexpr int B_FULL2 = B_EMPTY1 + 32;
constexpr int B_EMPTY2 = B_FULL2 + 40;
constexpr int B_G = B_EMPTY2 + 40;
constexpr int B_PEER = B_G + 8;
constexpr int B_RECV = B_PEER + 8;
constexpr int B_XS = B_RECV + 64;
constexpr int B_COEF = B_XS + 8;
constexpr int SM_READY = B_COEF + 8;
constexpr int SM_G = SM_BAR + 512;
constexpr int SM_GW = SM_BAR + 1024;
constexpr int SMEM_BYTES = SM_GW + 2048;

constexpr size_t G_EPOCH = 0;
constexpr size_t G_FLAG_ACT = 1024;
constexpr size_t G_FLAG_H = G_FLAG_ACT + 2048;
constexpr size_t G_GATE = G_FLAG_H + 2048;
constexpr size_t G_AGG = G_GATE + 8192;
constexpr size_t G_H = G_AGG + NCG * NRB * 64 * 16 + 3072;
constexpr size_t G_ACT = G_H + (size_t)NRB * NCG * 2 * CH;
static_assert(G_H % 1024 == 0, "tile alignment");
__device__ __align__(1024) unsigned char g_scratch[G_ACT + (size_t)NRB * NFC * CH];

struct Params {
  unsigned char* scr;
  float* out;
  uint32_t zero;
  int use_smid;
  const __nv_bfloat16 *lre, *lim, *logdt, *dskip, *gatew;
  const char *p_cre, *p_cim, *p_wd, *p_wg, *p_wu, *p_bre, *p_bim;
  CUtensorMap x, wg, wu, bre, bim, cre, cim, wd, xs;
};

#define PROF_EV(i)
#define TR(it, f)
#define PROF_ARGS
#define PROF_T0
#define PROF_ACC(v)

__device__ __forceinline__ uint32_t smem_u32(const void* p) { return (uint32_t)__cvta_generic_to_shared(p); }
__device__ __forceinline__ bool elect_one() {
  uint32_t p;
  asm volatile("{\n.reg .pred p;\nelect.sync _|p, 0xffffffff;\nselp.u32 %0, 1, 0, p;\n}" : "=r"(p));
  return p != 0;
}
__device__ __forceinline__ void mbar_init(uint32_t bar, uint32_t cnt) {
  asm volatile("mbarrier.init.shared::cta.b64 [%0], %1;" ::"r"(bar), "r"(cnt) : "memory");
}
__device__ __forceinline__ void mbar_expect_tx(uint32_t bar, uint32_t bytes) {
  asm volatile("mbarrier.arrive.expect_tx.shared::cta.b64 _, [%0], %1;" ::"r"(bar), "r"(bytes) : "memory");
}
__device__ __forceinline__ void mbar_arrive(uint32_t bar) {
  asm volatile("mbarrier.arrive.shared::cta.b64 _, [%0];" ::"r"(bar) : "memory");
}
__device__ __forceinline__ uint32_t mapa(uint32_t addr, uint32_t cta) {
  uint32_t r;
  asm("mapa.shared::cluster.u32 %0, %1, %2;" : "=r"(r) : "r"(addr), "r"(cta));
  return r;
}
__device__ __forceinline__ void mbar_arrive_remote(uint32_t cluster_bar) {
  asm volatile("mbarrier.arrive.relaxed.cluster.shared::cluster.b64 _, [%0];" ::"r"(cluster_bar) : "memory");
}
__device__ __forceinline__ void mbar_wait(uint32_t bar, uint32_t parity) {
  asm volatile("{\n.reg .pred p;\n.reg .u32 c;\nmov.u32 c, 0;\n"
               "W:\nmbarrier.try_wait.parity.shared::cta.b64 p, [%0], %1;\n@p bra D;\n"
               "add.u32 c, c, 1;\nsetp.gt.u32 p, c, 1048576;\n@p trap;\nbra W;\nD:\n}"
               ::"r"(bar), "r"(parity) : "memory");
}
__device__ __forceinline__ void mbar_wait_cluster(uint32_t bar, uint32_t parity) {
  asm volatile("{\n.reg .pred p;\n.reg .u32 c;\nmov.u32 c, 0;\n"
               "W:\nmbarrier.try_wait.parity.acquire.cluster.shared::cta.b64 p, [%0], %1;\n@p bra D;\n"
               "add.u32 c, c, 1;\nsetp.gt.u32 p, c, 1048576;\n@p trap;\nbra W;\nD:\n}"
               ::"r"(bar), "r"(parity) : "memory");
}
__device__ __forceinline__ uint32_t mbar_test(uint32_t bar, uint32_t parity) {
  uint32_t ok;
  asm volatile("{\n.reg .pred p;\nmbarrier.test_wait.parity.shared::cta.b64 p, [%1], %2;\nselp.u32 %0, 1, 0, p;\n}"
               : "=r"(ok) : "r"(bar), "r"(parity) : "memory");
  return ok;
}
__device__ __forceinline__ void mbar_arrive_elect(uint32_t bar) {
  asm volatile("{\n.reg .pred p;\nelect.sync _|p, 0xffffffff;\n@p mbarrier.arrive.shared::cta.b64 _, [%0];\n}" ::"r"(bar) : "memory");
}
__device__ __forceinline__ float mbar_arrive_token(uint32_t bar) {
  uint32_t lo;
  asm volatile("{\n.reg .pred p;\n.reg .b64 st;\n.reg .b32 hi;\nmov.b64 st, 0;\nelect.sync _|p, 0xffffffff;\n"
               "@p mbarrier.arrive.shared::cta.b64 st, [%1];\nmov.b64 {%0, hi}, st;\n}" : "=r"(lo) : "r"(bar) : "memory");
  return __uint_as_float(lo);
}
__device__ __forceinline__ void trap_if_over(int n, int limit) {
  asm volatile("{\n.reg .pred p;\nsetp.gt.s32 p, %0, %1;\n@p trap;\n}" ::"r"(n), "r"(limit));
}
__device__ __forceinline__ void bulk_load(uint32_t dst, const void* src, uint32_t bytes, uint32_t bar) {
  asm volatile("cp.async.bulk.shared::cluster.global.mbarrier::complete_tx::bytes [%0], [%1], %2, [%3];"
               ::"r"(dst), "l"(src), "r"(bytes), "r"(bar) : "memory");
}
__device__ __forceinline__ void tma2d(uint32_t dst, const CUtensorMap* m, int c0, int c1, uint32_t bar) {
  asm volatile("cp.async.bulk.tensor.2d.shared::cluster.global.mbarrier::complete_tx::bytes [%0], [%1, {%3, %4}], [%2];"
               ::"r"(dst), "l"(m), "r"(bar), "r"(c0), "r"(c1) : "memory");
}
__device__ __forceinline__ void tma5d(uint32_t dst, const CUtensorMap* m, int c0, int c4, uint32_t bar) {
  asm volatile("cp.async.bulk.tensor.5d.shared::cluster.global.mbarrier::complete_tx::bytes [%0], [%1, {%3, %5, %5, %5, %4}], [%2];"
               ::"r"(dst), "l"(m), "r"(bar), "r"(c0), "r"(c4), "r"(0) : "memory");
}
__device__ __forceinline__ void l2_prefetch(const void* p, uint32_t bytes) {
  asm volatile("cp.async.bulk.prefetch.L2.global [%0], %1;" ::"l"(p), "r"(bytes) : "memory");
}
__device__ __forceinline__ void prefetch_map(const CUtensorMap* m) {
  asm volatile("prefetch.tensormap [%0];" ::"l"(m) : "memory");
}
__device__ __forceinline__ void wg_fence() { asm volatile("wgmma.fence.sync.aligned;" ::: "memory"); }
__device__ __forceinline__ void wg_commit() { asm volatile("wgmma.commit_group.sync.aligned;" ::: "memory"); }
template <int N> __device__ __forceinline__ void wg_wait() { asm volatile("wgmma.wait_group.sync.aligned %0;" ::"n"(N) : "memory"); }
template <int R> __device__ __forceinline__ void fence_regs(float (&d)[R]) {
#pragma unroll
  for (int i = 0; i < R; i++) asm volatile("" : "+f"(d[i])::"memory");
}
__device__ __forceinline__ uint64_t desc_k(uint32_t a16) { return ((uint64_t)0x40000040u << 32) | (uint64_t)(a16 + (1u << 16)); }
__device__ __forceinline__ uint64_t desc_mn(uint32_t a16) { return ((uint64_t)0x40000040u << 32) | (uint64_t)(a16 + (512u << 16)); }
__device__ __forceinline__ void bar_sync(int id, int n) { asm volatile("bar.sync %0, %1;" ::"r"(id), "r"(n) : "memory"); }
__device__ __forceinline__ void bar_arrive(int id, int n) { asm volatile("bar.arrive %0, %1;" ::"r"(id), "r"(n) : "memory"); }
__device__ __forceinline__ uint32_t pack_bf16(float lo, float hi) {
  uint32_t r;
  asm("cvt.rn.bf16x2.f32 %0, %1, %2;" : "=r"(r) : "f"(hi), "f"(lo));
  return r;
}
__device__ __forceinline__ float bf_lo(uint32_t v) { return __uint_as_float(v << 16); }
__device__ __forceinline__ float bf_hi(uint32_t v) { return __uint_as_float(v & 0xFFFF0000u); }
__device__ __forceinline__ void st_v4(void* p, uint32_t a, uint32_t b, uint32_t c, uint32_t d) {
  asm volatile("st.global.v4.b32 [%0], {%1, %2, %3, %4};" ::"l"(p), "r"(a), "r"(b), "r"(c), "r"(d) : "memory");
}
__device__ __forceinline__ float fast_ex2(float x) { float y; asm("ex2.approx.ftz.f32 %0, %1;" : "=f"(y) : "f"(x)); return y; }
__device__ __forceinline__ float fast_rcp(float x) { float y; asm("rcp.approx.ftz.f32 %0, %1;" : "=f"(y) : "f"(x)); return y; }
struct cplx { float r, i; };
__device__ __forceinline__ cplx cmul(cplx a, cplx b) { return {a.r * b.r - a.i * b.i, a.r * b.i + a.i * b.r}; }
__device__ __forceinline__ cplx cfma(cplx a, cplx b, cplx c) {
  return {fmaf(a.r, b.r, fmaf(-a.i, b.i, c.r)), fmaf(a.r, b.i, fmaf(a.i, b.r, c.i))};
}
__device__ __forceinline__ cplx cshfl_up(cplx a, int d) {
  return {__shfl_up_sync(0xffffffffu, a.r, d, 4), __shfl_up_sync(0xffffffffu, a.i, d, 4)};
}

template <int TA, int TB>
__device__ __forceinline__ void wgmma_n8(float (&d)[4], uint64_t da, uint64_t db, int scale_d) {
  asm volatile("{\n.reg .pred p;\nsetp.ne.b32 p, %6, 0;\n"
    "wgmma.mma_async.sync.aligned.m64n8k16.f32.bf16.bf16 {"
    "%0, %1, %2, %3"
    "}, %4, %5, p, 1, 1, %7, %8;\n}\n"
    : "+f"(d[0]), "+f"(d[1]), "+f"(d[2]), "+f"(d[3])
    : "l"(da), "l"(db), "r"(scale_d), "n"(TA), "n"(TB));
}
template <int TA, int TB>
__device__ __forceinline__ void wgmma_n8_z(float (&d)[4], uint64_t da, uint64_t db) {
  asm volatile("{\n.reg .pred p;\nsetp.ne.b32 p, 0, 0;\n"
    "wgmma.mma_async.sync.aligned.m64n8k16.f32.bf16.bf16 {"
    "%0, %1, %2, %3"
    "}, %4, %5, p, 1, 1, %6, %7;\n}\n"
    : "=f"(d[0]), "=f"(d[1]), "=f"(d[2]), "=f"(d[3])
    : "l"(da), "l"(db), "n"(TA), "n"(TB));
}

template <int TA, int TB>
__device__ __forceinline__ void wgmma_n64(float (&d)[32], uint64_t da, uint64_t db, int scale_d) {
  asm volatile("{\n.reg .pred p;\nsetp.ne.b32 p, %34, 0;\n"
    "wgmma.mma_async.sync.aligned.m64n64k16.f32.bf16.bf16 {"
    "%0, %1, %2, %3, %4, %5, %6, %7, %8, %9, %10, %11, %12, %13, %14, %15, "
    "%16, %17, %18, %19, %20, %21, %22, %23, %24, %25, %26, %27, %28, %29, %30, %31"
    "}, %32, %33, p, 1, 1, %35, %36;\n}\n"
    : "+f"(d[0]), "+f"(d[1]), "+f"(d[2]), "+f"(d[3]), "+f"(d[4]), "+f"(d[5]), "+f"(d[6]), "+f"(d[7]),
      "+f"(d[8]), "+f"(d[9]), "+f"(d[10]), "+f"(d[11]), "+f"(d[12]), "+f"(d[13]), "+f"(d[14]), "+f"(d[15]),
      "+f"(d[16]), "+f"(d[17]), "+f"(d[18]), "+f"(d[19]), "+f"(d[20]), "+f"(d[21]), "+f"(d[22]), "+f"(d[23]),
      "+f"(d[24]), "+f"(d[25]), "+f"(d[26]), "+f"(d[27]), "+f"(d[28]), "+f"(d[29]), "+f"(d[30]), "+f"(d[31])
    : "l"(da), "l"(db), "r"(scale_d), "n"(TA), "n"(TB));
}
template <int TA, int TB>
__device__ __forceinline__ void wgmma_n64_z(float (&d)[32], uint64_t da, uint64_t db) {
  asm volatile("{\n.reg .pred p;\nsetp.ne.b32 p, 0, 0;\n"
    "wgmma.mma_async.sync.aligned.m64n64k16.f32.bf16.bf16 {"
    "%0, %1, %2, %3, %4, %5, %6, %7, %8, %9, %10, %11, %12, %13, %14, %15, "
    "%16, %17, %18, %19, %20, %21, %22, %23, %24, %25, %26, %27, %28, %29, %30, %31"
    "}, %32, %33, p, 1, 1, %34, %35;\n}\n"
    : "=f"(d[0]), "=f"(d[1]), "=f"(d[2]), "=f"(d[3]), "=f"(d[4]), "=f"(d[5]), "=f"(d[6]), "=f"(d[7]),
      "=f"(d[8]), "=f"(d[9]), "=f"(d[10]), "=f"(d[11]), "=f"(d[12]), "=f"(d[13]), "=f"(d[14]), "=f"(d[15]),
      "=f"(d[16]), "=f"(d[17]), "=f"(d[18]), "=f"(d[19]), "=f"(d[20]), "=f"(d[21]), "=f"(d[22]), "=f"(d[23]),
      "=f"(d[24]), "=f"(d[25]), "=f"(d[26]), "=f"(d[27]), "=f"(d[28]), "=f"(d[29]), "=f"(d[30]), "=f"(d[31])
    : "l"(da), "l"(db), "n"(TA), "n"(TB));
}

template <int TA, int TB>
__device__ __forceinline__ void wgmma_n96(float (&d)[48], uint64_t da, uint64_t db, int scale_d) {
  asm volatile("{\n.reg .pred p;\nsetp.ne.b32 p, %50, 0;\n"
    "wgmma.mma_async.sync.aligned.m64n96k16.f32.bf16.bf16 {"
    "%0, %1, %2, %3, %4, %5, %6, %7, %8, %9, %10, %11, %12, %13, %14, %15, "
    "%16, %17, %18, %19, %20, %21, %22, %23, %24, %25, %26, %27, %28, %29, %30, %31, "
    "%32, %33, %34, %35, %36, %37, %38, %39, %40, %41, %42, %43, %44, %45, %46, %47"
    "}, %48, %49, p, 1, 1, %51, %52;\n}\n"
    : "+f"(d[0]), "+f"(d[1]), "+f"(d[2]), "+f"(d[3]), "+f"(d[4]), "+f"(d[5]), "+f"(d[6]), "+f"(d[7]),
      "+f"(d[8]), "+f"(d[9]), "+f"(d[10]), "+f"(d[11]), "+f"(d[12]), "+f"(d[13]), "+f"(d[14]), "+f"(d[15]),
      "+f"(d[16]), "+f"(d[17]), "+f"(d[18]), "+f"(d[19]), "+f"(d[20]), "+f"(d[21]), "+f"(d[22]), "+f"(d[23]),
      "+f"(d[24]), "+f"(d[25]), "+f"(d[26]), "+f"(d[27]), "+f"(d[28]), "+f"(d[29]), "+f"(d[30]), "+f"(d[31]),
      "+f"(d[32]), "+f"(d[33]), "+f"(d[34]), "+f"(d[35]), "+f"(d[36]), "+f"(d[37]), "+f"(d[38]), "+f"(d[39]),
      "+f"(d[40]), "+f"(d[41]), "+f"(d[42]), "+f"(d[43]), "+f"(d[44]), "+f"(d[45]), "+f"(d[46]), "+f"(d[47])
    : "l"(da), "l"(db), "r"(scale_d), "n"(TA), "n"(TB));
}
template <int TA, int TB>
__device__ __forceinline__ void wgmma_n96_z(float (&d)[48], uint64_t da, uint64_t db) {
  asm volatile("{\n.reg .pred p;\nsetp.ne.b32 p, 0, 0;\n"
    "wgmma.mma_async.sync.aligned.m64n96k16.f32.bf16.bf16 {"
    "%0, %1, %2, %3, %4, %5, %6, %7, %8, %9, %10, %11, %12, %13, %14, %15, "
    "%16, %17, %18, %19, %20, %21, %22, %23, %24, %25, %26, %27, %28, %29, %30, %31, "
    "%32, %33, %34, %35, %36, %37, %38, %39, %40, %41, %42, %43, %44, %45, %46, %47"
    "}, %48, %49, p, 1, 1, %50, %51;\n}\n"
    : "=f"(d[0]), "=f"(d[1]), "=f"(d[2]), "=f"(d[3]), "=f"(d[4]), "=f"(d[5]), "=f"(d[6]), "=f"(d[7]),
      "=f"(d[8]), "=f"(d[9]), "=f"(d[10]), "=f"(d[11]), "=f"(d[12]), "=f"(d[13]), "=f"(d[14]), "=f"(d[15]),
      "=f"(d[16]), "=f"(d[17]), "=f"(d[18]), "=f"(d[19]), "=f"(d[20]), "=f"(d[21]), "=f"(d[22]), "=f"(d[23]),
      "=f"(d[24]), "=f"(d[25]), "=f"(d[26]), "=f"(d[27]), "=f"(d[28]), "=f"(d[29]), "=f"(d[30]), "=f"(d[31]),
      "=f"(d[32]), "=f"(d[33]), "=f"(d[34]), "=f"(d[35]), "=f"(d[36]), "=f"(d[37]), "=f"(d[38]), "=f"(d[39]),
      "=f"(d[40]), "=f"(d[41]), "=f"(d[42]), "=f"(d[43]), "=f"(d[44]), "=f"(d[45]), "=f"(d[46]), "=f"(d[47])
    : "l"(da), "l"(db), "n"(TA), "n"(TB));
}

template <int TA, int TB>
__device__ __forceinline__ void wgmma_n128(float (&d)[64], uint64_t da, uint64_t db, int scale_d) {
  asm volatile("{\n.reg .pred p;\nsetp.ne.b32 p, %66, 0;\n"
    "wgmma.mma_async.sync.aligned.m64n128k16.f32.bf16.bf16 {"
    "%0, %1, %2, %3, %4, %5, %6, %7, %8, %9, %10, %11, %12, %13, %14, %15, "
    "%16, %17, %18, %19, %20, %21, %22, %23, %24, %25, %26, %27, %28, %29, %30, %31, "
    "%32, %33, %34, %35, %36, %37, %38, %39, %40, %41, %42, %43, %44, %45, %46, %47, "
    "%48, %49, %50, %51, %52, %53, %54, %55, %56, %57, %58, %59, %60, %61, %62, %63"
    "}, %64, %65, p, 1, 1, %67, %68;\n}\n"
    : "+f"(d[0]), "+f"(d[1]), "+f"(d[2]), "+f"(d[3]), "+f"(d[4]), "+f"(d[5]), "+f"(d[6]), "+f"(d[7]),
      "+f"(d[8]), "+f"(d[9]), "+f"(d[10]), "+f"(d[11]), "+f"(d[12]), "+f"(d[13]), "+f"(d[14]), "+f"(d[15]),
      "+f"(d[16]), "+f"(d[17]), "+f"(d[18]), "+f"(d[19]), "+f"(d[20]), "+f"(d[21]), "+f"(d[22]), "+f"(d[23]),
      "+f"(d[24]), "+f"(d[25]), "+f"(d[26]), "+f"(d[27]), "+f"(d[28]), "+f"(d[29]), "+f"(d[30]), "+f"(d[31]),
      "+f"(d[32]), "+f"(d[33]), "+f"(d[34]), "+f"(d[35]), "+f"(d[36]), "+f"(d[37]), "+f"(d[38]), "+f"(d[39]),
      "+f"(d[40]), "+f"(d[41]), "+f"(d[42]), "+f"(d[43]), "+f"(d[44]), "+f"(d[45]), "+f"(d[46]), "+f"(d[47]),
      "+f"(d[48]), "+f"(d[49]), "+f"(d[50]), "+f"(d[51]), "+f"(d[52]), "+f"(d[53]), "+f"(d[54]), "+f"(d[55]),
      "+f"(d[56]), "+f"(d[57]), "+f"(d[58]), "+f"(d[59]), "+f"(d[60]), "+f"(d[61]), "+f"(d[62]), "+f"(d[63])
    : "l"(da), "l"(db), "r"(scale_d), "n"(TA), "n"(TB));
}
template <int TA, int TB>
__device__ __forceinline__ void wgmma_n128_z(float (&d)[64], uint64_t da, uint64_t db) {
  asm volatile("{\n.reg .pred p;\nsetp.ne.b32 p, 0, 0;\n"
    "wgmma.mma_async.sync.aligned.m64n128k16.f32.bf16.bf16 {"
    "%0, %1, %2, %3, %4, %5, %6, %7, %8, %9, %10, %11, %12, %13, %14, %15, "
    "%16, %17, %18, %19, %20, %21, %22, %23, %24, %25, %26, %27, %28, %29, %30, %31, "
    "%32, %33, %34, %35, %36, %37, %38, %39, %40, %41, %42, %43, %44, %45, %46, %47, "
    "%48, %49, %50, %51, %52, %53, %54, %55, %56, %57, %58, %59, %60, %61, %62, %63"
    "}, %64, %65, p, 1, 1, %66, %67;\n}\n"
    : "=f"(d[0]), "=f"(d[1]), "=f"(d[2]), "=f"(d[3]), "=f"(d[4]), "=f"(d[5]), "=f"(d[6]), "=f"(d[7]),
      "=f"(d[8]), "=f"(d[9]), "=f"(d[10]), "=f"(d[11]), "=f"(d[12]), "=f"(d[13]), "=f"(d[14]), "=f"(d[15]),
      "=f"(d[16]), "=f"(d[17]), "=f"(d[18]), "=f"(d[19]), "=f"(d[20]), "=f"(d[21]), "=f"(d[22]), "=f"(d[23]),
      "=f"(d[24]), "=f"(d[25]), "=f"(d[26]), "=f"(d[27]), "=f"(d[28]), "=f"(d[29]), "=f"(d[30]), "=f"(d[31]),
      "=f"(d[32]), "=f"(d[33]), "=f"(d[34]), "=f"(d[35]), "=f"(d[36]), "=f"(d[37]), "=f"(d[38]), "=f"(d[39]),
      "=f"(d[40]), "=f"(d[41]), "=f"(d[42]), "=f"(d[43]), "=f"(d[44]), "=f"(d[45]), "=f"(d[46]), "=f"(d[47]),
      "=f"(d[48]), "=f"(d[49]), "=f"(d[50]), "=f"(d[51]), "=f"(d[52]), "=f"(d[53]), "=f"(d[54]), "=f"(d[55]),
      "=f"(d[56]), "=f"(d[57]), "=f"(d[58]), "=f"(d[59]), "=f"(d[60]), "=f"(d[61]), "=f"(d[62]), "=f"(d[63])
    : "l"(da), "l"(db), "n"(TA), "n"(TB));
}

template <int TA, int TB>
__device__ __forceinline__ void wgmma_n160(float (&d)[80], uint64_t da, uint64_t db, int scale_d) {
  asm volatile("{\n.reg .pred p;\nsetp.ne.b32 p, %82, 0;\n"
    "wgmma.mma_async.sync.aligned.m64n160k16.f32.bf16.bf16 {"
    "%0, %1, %2, %3, %4, %5, %6, %7, %8, %9, %10, %11, %12, %13, %14, %15, "
    "%16, %17, %18, %19, %20, %21, %22, %23, %24, %25, %26, %27, %28, %29, %30, %31, "
    "%32, %33, %34, %35, %36, %37, %38, %39, %40, %41, %42, %43, %44, %45, %46, %47, "
    "%48, %49, %50, %51, %52, %53, %54, %55, %56, %57, %58, %59, %60, %61, %62, %63, "
    "%64, %65, %66, %67, %68, %69, %70, %71, %72, %73, %74, %75, %76, %77, %78, %79"
    "}, %80, %81, p, 1, 1, %83, %84;\n}\n"
    : "+f"(d[0]), "+f"(d[1]), "+f"(d[2]), "+f"(d[3]), "+f"(d[4]), "+f"(d[5]), "+f"(d[6]), "+f"(d[7]),
      "+f"(d[8]), "+f"(d[9]), "+f"(d[10]), "+f"(d[11]), "+f"(d[12]), "+f"(d[13]), "+f"(d[14]), "+f"(d[15]),
      "+f"(d[16]), "+f"(d[17]), "+f"(d[18]), "+f"(d[19]), "+f"(d[20]), "+f"(d[21]), "+f"(d[22]), "+f"(d[23]),
      "+f"(d[24]), "+f"(d[25]), "+f"(d[26]), "+f"(d[27]), "+f"(d[28]), "+f"(d[29]), "+f"(d[30]), "+f"(d[31]),
      "+f"(d[32]), "+f"(d[33]), "+f"(d[34]), "+f"(d[35]), "+f"(d[36]), "+f"(d[37]), "+f"(d[38]), "+f"(d[39]),
      "+f"(d[40]), "+f"(d[41]), "+f"(d[42]), "+f"(d[43]), "+f"(d[44]), "+f"(d[45]), "+f"(d[46]), "+f"(d[47]),
      "+f"(d[48]), "+f"(d[49]), "+f"(d[50]), "+f"(d[51]), "+f"(d[52]), "+f"(d[53]), "+f"(d[54]), "+f"(d[55]),
      "+f"(d[56]), "+f"(d[57]), "+f"(d[58]), "+f"(d[59]), "+f"(d[60]), "+f"(d[61]), "+f"(d[62]), "+f"(d[63]),
      "+f"(d[64]), "+f"(d[65]), "+f"(d[66]), "+f"(d[67]), "+f"(d[68]), "+f"(d[69]), "+f"(d[70]), "+f"(d[71]),
      "+f"(d[72]), "+f"(d[73]), "+f"(d[74]), "+f"(d[75]), "+f"(d[76]), "+f"(d[77]), "+f"(d[78]), "+f"(d[79])
    : "l"(da), "l"(db), "r"(scale_d), "n"(TA), "n"(TB));
}
template <int TA, int TB>
__device__ __forceinline__ void wgmma_n160_z(float (&d)[80], uint64_t da, uint64_t db) {
  asm volatile("{\n.reg .pred p;\nsetp.ne.b32 p, 0, 0;\n"
    "wgmma.mma_async.sync.aligned.m64n160k16.f32.bf16.bf16 {"
    "%0, %1, %2, %3, %4, %5, %6, %7, %8, %9, %10, %11, %12, %13, %14, %15, "
    "%16, %17, %18, %19, %20, %21, %22, %23, %24, %25, %26, %27, %28, %29, %30, %31, "
    "%32, %33, %34, %35, %36, %37, %38, %39, %40, %41, %42, %43, %44, %45, %46, %47, "
    "%48, %49, %50, %51, %52, %53, %54, %55, %56, %57, %58, %59, %60, %61, %62, %63, "
    "%64, %65, %66, %67, %68, %69, %70, %71, %72, %73, %74, %75, %76, %77, %78, %79"
    "}, %80, %81, p, 1, 1, %82, %83;\n}\n"
    : "=f"(d[0]), "=f"(d[1]), "=f"(d[2]), "=f"(d[3]), "=f"(d[4]), "=f"(d[5]), "=f"(d[6]), "=f"(d[7]),
      "=f"(d[8]), "=f"(d[9]), "=f"(d[10]), "=f"(d[11]), "=f"(d[12]), "=f"(d[13]), "=f"(d[14]), "=f"(d[15]),
      "=f"(d[16]), "=f"(d[17]), "=f"(d[18]), "=f"(d[19]), "=f"(d[20]), "=f"(d[21]), "=f"(d[22]), "=f"(d[23]),
      "=f"(d[24]), "=f"(d[25]), "=f"(d[26]), "=f"(d[27]), "=f"(d[28]), "=f"(d[29]), "=f"(d[30]), "=f"(d[31]),
      "=f"(d[32]), "=f"(d[33]), "=f"(d[34]), "=f"(d[35]), "=f"(d[36]), "=f"(d[37]), "=f"(d[38]), "=f"(d[39]),
      "=f"(d[40]), "=f"(d[41]), "=f"(d[42]), "=f"(d[43]), "=f"(d[44]), "=f"(d[45]), "=f"(d[46]), "=f"(d[47]),
      "=f"(d[48]), "=f"(d[49]), "=f"(d[50]), "=f"(d[51]), "=f"(d[52]), "=f"(d[53]), "=f"(d[54]), "=f"(d[55]),
      "=f"(d[56]), "=f"(d[57]), "=f"(d[58]), "=f"(d[59]), "=f"(d[60]), "=f"(d[61]), "=f"(d[62]), "=f"(d[63]),
      "=f"(d[64]), "=f"(d[65]), "=f"(d[66]), "=f"(d[67]), "=f"(d[68]), "=f"(d[69]), "=f"(d[70]), "=f"(d[71]),
      "=f"(d[72]), "=f"(d[73]), "=f"(d[74]), "=f"(d[75]), "=f"(d[76]), "=f"(d[77]), "=f"(d[78]), "=f"(d[79])
    : "l"(da), "l"(db), "n"(TA), "n"(TB));
}

__device__ __forceinline__ unsigned load_epoch(const Params& P, int role) {
  unsigned tag;
  asm volatile("ld.relaxed.gpu.global.u32 %0, [%1];" : "=r"(tag) : "l"(P.scr + G_EPOCH + 4 * role) : "memory");
  return tag;
}

__device__ __forceinline__ int unit_of(int ftype, int nt, int s, bool& ssm) {
  const int c = ftype * 4 + nt;
  ssm = false;
  if (s == 0) return c;
  if (s == 1) { ssm = true; return c; }
  if (s == 2) {
    if (!ftype) return 10 + nt;
    ssm = nt < 2;
    return ssm ? 8 + nt : 6 + nt;
  }
  if (s == 3) return 14 + c;
  return 23 + nt;
}

template <int MODE, bool ZERO>
__device__ __forceinline__ void unit_mma(float (&acc0)[64], float (&acc1)[64], float (&g0)[4], float (&g1)[4], uint32_t xa,
                                         uint32_t wa, uint32_t ga, int kk) {
  if (MODE == 1) {
    const uint64_t db = desc_k(xa + kk * 2);
    if (ZERO) { wgmma_n128_z<0, 0>(acc0, desc_k(wa), db); wgmma_n128_z<0, 0>(acc1, desc_k(wa + 512), db); }
    else { wgmma_n128<0, 0>(acc0, desc_k(wa + kk * 2), db, 1); wgmma_n128<0, 0>(acc1, desc_k(wa + 512 + kk * 2), db, 1); }
  } else {
    const uint64_t db = desc_mn(wa + kk * 128);
    if (ZERO) { wgmma_n128_z<0, 1>(acc0, desc_k(xa), db); wgmma_n128_z<0, 1>(acc1, desc_k(xa + 512), db); }
    else { wgmma_n128<0, 1>(acc0, desc_k(xa + kk * 2), db, 1); wgmma_n128<0, 1>(acc1, desc_k(xa + 512 + kk * 2), db, 1); }
    if (MODE == 2) {
      const uint64_t dg = ((uint64_t)1 << 32) | (uint64_t)(ga + kk * 2 + (1u << 16));
      if (ZERO) { wgmma_n8_z<0, 0>(g0, desc_k(xa), dg); wgmma_n8_z<0, 0>(g1, desc_k(xa + 512), dg); }
      else { wgmma_n8<0, 0>(g0, desc_k(xa + kk * 2), dg, 1); wgmma_n8<0, 0>(g1, desc_k(xa + 512 + kk * 2), dg, 1); }
    }
  }
}
template <int MODE>
__device__ __forceinline__ void unit_fence(float (&acc0)[64], float (&acc1)[64], float (&g0)[4], float (&g1)[4]) {
  fence_regs(acc0); fence_regs(acc1);
  if (MODE == 2) { fence_regs(g0); fence_regs(g1); }
}
template <int MODE, bool K0>
__device__ __forceinline__ uint32_t unit_kstep(float (&acc0)[64], float (&acc1)[64], float (&g0)[4], float (&g1)[4], uint32_t sb,
                                               int k, uint32_t& s, uint32_t& ph, bool first) {
  const uint32_t sb16 = (sb & 0x3FFFFu) >> 4;
  const uint32_t res = sb16 + (SM_RES >> 4) + k * (CH >> 4), ring = sb16 + (SM_RING >> 4) + s * (CH >> 4);
  const uint32_t xa = MODE == 2 ? ring : res, wa = MODE == 2 ? res : ring, ga = sb16 + (SM_GW >> 4) + k * 8;
  const uint32_t sp = (s + 3) & 3;
  s = (s + 1) & 3;
  ph ^= (s == 0);
  if (!K0) unit_fence<MODE>(acc0, acc1, g0, g1);
  wg_fence();
  unit_mma<MODE, K0>(acc0, acc1, g0, g1, xa, wa, ga, 0);
  unit_mma<MODE, false>(acc0, acc1, g0, g1, xa, wa, ga, 1);
  wg_commit();
  if (!K0) {
    wg_wait<1>();
    mbar_arrive_elect(sb + B_EMPTY1 + 8 * sp);
  }
  uint32_t ok = mbar_test(sb + B_FULL1 + 8 * s, ph);
  if (first) ok &= mbar_test(sb + B_XFULL + 8 * (k + 1), 0);
  unit_fence<MODE>(acc0, acc1, g0, g1);
  wg_fence();
  unit_mma<MODE, false>(acc0, acc1, g0, g1, xa, wa, ga, 2);
  unit_mma<MODE, false>(acc0, acc1, g0, g1, xa, wa, ga, 3);
  wg_commit();
  unit_fence<MODE>(acc0, acc1, g0, g1);
  return ok;
}
template <int MODE>
__device__ __forceinline__ float unit_mainloop(float (&acc0)[64], float (&acc1)[64], float (&g0)[4], float (&g1)[4], uint32_t sb,
                                              int it0, bool first, bool signal, int wg, int lane
) {
  uint32_t s = it0 & 3, ph = (it0 >> 2) & 1;
  if (first) mbar_wait(sb + B_XFULL, 0);
  mbar_wait(sb + B_FULL1 + 8 * s, ph);
  if ((threadIdx.x & 127) == 0) TR(it0, 2);
  if (it0 == 0) PROF_EV(55);
  uint32_t ok = unit_kstep<MODE, true>(acc0, acc1, g0, g1, sb, 0, s, ph, first);
#pragma unroll 1
  for (int k = 1; k < 10; k++) {
    if ((threadIdx.x & 127) == 0) TR(it0 + k, 1);
    if (!ok) {
      if (first) mbar_wait(sb + B_XFULL + 8 * k, 0);
      mbar_wait(sb + B_FULL1 + 8 * s, ph);
    }
    if ((threadIdx.x & 127) == 0) TR(it0 + k, 2);
    ok = unit_kstep<MODE, false>(acc0, acc1, g0, g1, sb, k, s, ph, first);
  }
  if (signal) bar_arrive(1 + (wg ^ 1), 256);
  wg_wait<0>();
  unit_fence<MODE>(acc0, acc1, g0, g1);
  return mbar_arrive_token(sb + B_EMPTY1 + 8 * ((s + 3) & 3));
}

__device__ __forceinline__ float chain(float x, float y, uint32_t zero) {
  return __uint_as_float(__float_as_uint(x) | (__float_as_uint(y) & zero));
}

template <bool PACED, int PIECE>
__device__ __forceinline__ void ffn_piece(const float (&a0)[64], const float (&a1)[64], unsigned char* tile, int w, int lane,
                                          float (&v)[NCH], uint32_t zero) {
  constexpr int mh = PIECE >> 2, hi = (PIECE >> 1) & 1, h = PIECE & 1;
  const int q = lane & 3, r = lane >> 2;
  const int m7 = 4 * (w & 1) + 2 * hi + (r & 1);
  const int m = (2 * mh + (w >> 1)) * 32 + (r >> 1) * 8 + m7;
  uint32_t p[4];
#pragma unroll
  for (int j = 0; j < 4; j++) {
    float o[2];
#pragma unroll
    for (int e = 0; e < 2; e++) {
      const int i = 4 * (4 * h + j) + 2 * hi + e, c = (8 * PIECE + 2 * j + e) % NCH;
      const float g = mh ? a1[i] : a0[i], u = mh ? a1[32 + i] : a0[32 + i];
      const float sg = fast_rcp(1.0f + fast_ex2(g * (PACED ? chain(-1.4426950408889634f, v[c], zero) : v[0])));
      o[e] = (g * sg) * u;
      if (PACED) v[c] = o[e];
    }
    p[j] = pack_bf16(o[0], o[1]);
  }
  st_v4(tile + m * 128 + (((4 * h + q) ^ m7) << 4), p[0], p[1], p[2], p[3]);
}
template <bool PACED, int N, int I = 0>
__device__ __forceinline__ void ffn_pieces(const float (&a0)[64], const float (&a1)[64], unsigned char* tile, int w, int lane,
                                           float (&v)[NCH], uint32_t zero) {
  if constexpr (I < N) {
    ffn_piece<PACED, I>(a0, a1, tile, w, lane, v, zero);
    ffn_pieces<PACED, N, I + 1>(a0, a1, tile, w, lane, v, zero);
  }
}

struct SsmCoef { cplx lam, c, l32, l64, mu; };
__device__ __forceinline__ float4 ssm_coef(const Params& P, int p) {
  const float lr = __bfloat162float(P.lre[p]), li = __bfloat162float(P.lim[p]);
  const float dt = __bfloat162float(__float2bfloat16_rn(expf(__bfloat162float(P.logdt[p]))));
  float sn, cs;
  sincosf(dt * li, &sn, &cs);
  const float ex = expf(dt * lr);
  const float nr = ex * cs - 1.0f, ni = ex * sn, den = 1.0f / (lr * lr + li * li);
  return make_float4(ex * cs, ex * sn, (nr * lr + ni * li) * den, (ni * lr - nr * li) * den);
}
__device__ __forceinline__ SsmCoef ssm_powers(uint32_t addr) {
  SsmCoef o;
  asm volatile("ld.shared.v4.f32 {%0, %1, %2, %3}, [%4];" : "=f"(o.lam.r), "=f"(o.lam.i), "=f"(o.c.r), "=f"(o.c.i) : "r"(addr) : "memory");
  cplx t = o.lam;
#pragma unroll
  for (int i = 0; i < 5; i++) t = cmul(t, t);
  o.l32 = t;
  o.l64 = cmul(t, t);
  o.mu = cmul(o.l64, o.l64);
  return o;
}

__device__ __forceinline__ void agg_load(unsigned long long& a, unsigned long long& b, const void* p, int valid) {
  asm volatile("{\n.reg .pred p;\nsetp.ne.s32 p, %3, 0;\n@p ld.relaxed.gpu.global.v2.b64 {%0, %1}, [%2];\n}"
               : "+l"(a), "+l"(b) : "l"(p), "r"(valid) : "memory");
}

__device__ __forceinline__ void ssm_epilogue(const float (&vr)[64], const float (&vi)[64], const SsmCoef (&co)[2], unsigned char* scr, int rb,
                                             int cg, unsigned tag, int w, int lane, uint32_t zero, float prev
) {
  const int q = lane & 3, r = lane >> 2;
  char* agg = (char*)scr + G_AGG + ((cg * NRB + rb) * 64 + 16 * w + r) * 16;
  cplx s1[2];
#pragma unroll
  for (int hi = 0; hi < 2; hi++) {
    const cplx lam = P1DENSE && hi ? co[hi].lam : cplx{chain(co[hi].lam.r, prev, zero), chain(co[hi].lam.i, prev, zero)};
    cplx s = {vr[2 * hi], vi[2 * hi]};
#pragma unroll
    for (int t = 1; t < 32; t++) {
      const int i = 4 * (t >> 1) + 2 * hi + (t & 1);
      s = cfma(lam, s, cplx{vr[i], vi[i]});
    }
    s1[hi] = s;
    prev = s.r;
  }
#pragma unroll
  for (int hi = 0; hi < 2; hi++) {
    const cplx y = cshfl_up(s1[hi], 1);
    if (q >= 1) s1[hi] = cfma(co[hi].l32, y, s1[hi]);
  }
#pragma unroll
  for (int hi = 0; hi < 2; hi++) {
    const cplx y = cshfl_up(s1[hi], 2);
    if (q >= 2) s1[hi] = cfma(co[hi].l64, y, s1[hi]);
    const unsigned long long a = ((unsigned long long)tag << 32) | __float_as_uint(s1[hi].r);
    const unsigned long long b = ((unsigned long long)tag << 32) | __float_as_uint(s1[hi].i);
    asm volatile("{\n.reg .pred p;\nsetp.eq.s32 p, %3, 3;\n@p st.relaxed.gpu.global.v2.b64 [%0], {%1, %2};\n}"
                 ::"l"(agg + 128 * hi), "l"(a), "l"(b), "r"(q) : "memory");
  }
  PROF_EV(20 + slot * 2);
  cplx h0[2], mq[2], m4[2], lq[2];
#pragma unroll
  for (int hi = 0; hi < 2; hi++) {
    const cplx y = cshfl_up(s1[hi], 1), one = {1.f, 0.f};
    h0[hi] = q >= 1 ? cmul(co[hi].c, y) : cplx{0.f, 0.f};
    prev = y.i;
    const cplx mu2 = cmul(co[hi].mu, co[hi].mu);
    m4[hi] = cmul(mu2, mu2);
    mq[hi] = cmul((q & 1) ? co[hi].mu : one, (q & 2) ? mu2 : one);
    lq[hi] = cmul(cmul((q & 1) ? co[hi].l32 : one, (q & 2) ? co[hi].l64 : one), co[hi].c);
  }
  const int nv = rb - q;
  const char* src = agg - (1 + q) * 1024;
  unsigned long long ea[2][4], eb[2][4];
  float wr[64], wn[64];
#pragma unroll
  for (int t = 0; t < 64; t++) {
    if (t == GATHER_AT) {
      const char* sp = src + (__float_as_uint(prev) & zero);
#pragma unroll
      for (int m = 0; m < 4; m++)
#pragma unroll
        for (int h2 = 0; h2 < 2; h2++) {
          asm volatile("{\n.reg .pred p;\nsetp.ne.s32 p, %3, 0;\n@p ld.relaxed.gpu.global.v2.b64 {%0, %1}, [%2];\n}"
                       : "=l"(ea[h2][m]), "=l"(eb[h2][m]) : "l"(sp + 128 * h2 - 4096 * m), "r"((int)(4 * m < nv)) : "memory");
        }
    }
    const int hi = t >> 5, i = 4 * ((t & 31) >> 1) + 2 * hi + (t & 1);
    const float cr = t % PMCH == 0 ? chain(co[hi].c.r, prev, zero) : prev, ci = co[hi].c.i, a = vr[i], b = vi[i];
    wr[i] = fmaf(-ci, b, cr * a);
    wn[i] = fmaf(-ci, a, -cr * b);
    prev = (t + 1) % PMCH == 0 ? wr[i] : cr;
  }
  int spin = 0;
  while (true) {
    bool ok = true;
#pragma unroll
    for (int m = 0; m < 4; m++) {
      const unsigned x = ((unsigned)(ea[0][m] >> 32) ^ tag) | ((unsigned)(eb[0][m] >> 32) ^ tag) |
                         ((unsigned)(ea[1][m] >> 32) ^ tag) | ((unsigned)(eb[1][m] >> 32) ^ tag);
      ok = ok && (x == 0 || 4 * m >= nv);
    }
    if (__all_sync(0xffffffffu, ok)) break;
#pragma unroll
    for (int m = 0; m < 4; m++)
#pragma unroll
      for (int hi = 0; hi < 2; hi++) agg_load(ea[hi][m], eb[hi][m], src + 128 * hi - 4096 * m, 4 * m < nv);
    trap_if_over(++spin, 1 << 21);
  }
  PROF_EV(21 + slot * 2);
#pragma unroll
  for (int hi = 0; hi < 2; hi++) {
    cplx a = {0.f, 0.f};
#pragma unroll
    for (int m = 3; m >= 0; m--)
      if (4 * m < nv) a = cfma(m4[hi], a, cplx{__uint_as_float((unsigned)ea[hi][m]), __uint_as_float((unsigned)eb[hi][m])});
    a = cmul(a, mq[hi]);
    a.r += __shfl_xor_sync(0xffffffffu, a.r, 1); a.i += __shfl_xor_sync(0xffffffffu, a.i, 1);
    a.r += __shfl_xor_sync(0xffffffffu, a.r, 2); a.i += __shfl_xor_sync(0xffffffffu, a.i, 2);
    h0[hi] = cfma(lq[hi], a, h0[hi]);
  }
  unsigned char* tile = scr + G_H + (size_t)((rb * NCG + cg) * 2) * CH + (16 * w + r) * 128;
  unsigned char* t0 = tile + ((q ^ r) << 4);
  unsigned char* t1 = tile + (((4 + q) ^ r) << 4);
  prev = h0[1].i;
#pragma unroll
  for (int hi = 0; hi < 2; hi++) {
    const cplx lam = co[hi].lam;
    float hr = P2DENSE ? h0[hi].r : chain(h0[hi].r, prev, zero), hn = P2DENSE ? -h0[hi].i : chain(-h0[hi].i, prev, zero);
#pragma unroll
    for (int i8 = 0; i8 < 4; i8++) {
      uint32_t pr[4], pi[4];
#pragma unroll
      for (int jj = 0; jj < 4; jj++) {
        float fr[2], fn[2];
#pragma unroll
        for (int e = 0; e < 2; e++) {
          const int i = 4 * (4 * i8 + jj) + 2 * hi + e;
          const float nr = fmaf(lam.r, hr, fmaf(lam.i, hn, wr[i]));
          const float nn = fmaf(lam.r, hn, fmaf(-lam.i, hr, wn[i]));
          fr[e] = hr = nr; fn[e] = hn = nn;
        }
        pr[jj] = pack_bf16(fr[0], fr[1]);
        pi[jj] = pack_bf16(fn[0], fn[1]);
      }
      unsigned char* a = ((i8 & 1) ? t1 : t0) + (i8 >> 1) * 8192 + hi * 1024;
      st_v4(a, pr[0], pr[1], pr[2], pr[3]);
      st_v4(a + CH, pi[0], pi[1], pi[2], pi[3]);
      if (SF) hr = chain(hr, __uint_as_float(pr[0] | pr[1] | pr[2] | pr[3] | pi[0] | pi[1] | pi[2] | pi[3]), zero);
    }
    prev = hr;
  }
}

__device__ __forceinline__ void ldmatrix4(uint32_t* r, uint32_t addr) {
  asm volatile("ldmatrix.sync.aligned.m8n8.x4.shared.b16 {%0, %1, %2, %3}, [%4];"
               : "=r"(r[0]), "=r"(r[1]), "=r"(r[2]), "=r"(r[3]) : "r"(addr) : "memory");
}

template <bool F, bool K0, int NA>
__device__ __forceinline__ void p2_mma(float (&acc)[NA], float (&acb)[32], uint32_t a, uint32_t b, uint32_t lbo96) {
  if (!K0) { fence_regs(acc); if (F) fence_regs(acb); }
  wg_fence();
#pragma unroll
  for (int kk = 0; kk < 4; kk++) {
    if constexpr (F) {
      const uint64_t d96 = ((uint64_t)0x40000040u << 32) | (uint64_t)(b + kk * 128 + lbo96);
      if (K0 && kk == 0) { wgmma_n96_z<0, 1>(acc, desc_k(a), d96); wgmma_n64_z<0, 1>(acb, desc_k(a), desc_mn(b + 512)); }
      else { wgmma_n96<0, 1>(acc, desc_k(a + kk * 2), d96, 1); wgmma_n64<0, 1>(acb, desc_k(a + kk * 2), desc_mn(b + 512 + kk * 128), 1); }
    } else {
      if (K0 && kk == 0) wgmma_n160_z<1, 0>(acc, desc_mn(a), desc_k(b));
      else wgmma_n160<1, 0>(acc, desc_mn(a + kk * 128), desc_k(b + kk * 2), 1);
    }
  }
  wg_commit();
  fence_regs(acc);
  if (F) fence_regs(acb);
}

template <bool F>
__device__ __forceinline__ void phase2(const Params& P, uint32_t sb, int rb, int nt, int wg, int w, int lane,
                                       const float (&u0)[64], const float (&u1)[64], unsigned char* tile
) {
  constexpr int NK = F ? NFC : 2 * NCG;
  const int q = lane & 3, r = lane >> 2, warp = wg * 4 + w;
  if (elect_one()) mbar_expect_tx(sb + B_RECV + 8 * warp, 2560);
  asm volatile("barrier.cluster.wait.acquire.aligned;" ::: "memory");
  const uint32_t peer = F ? 0 : 1;
  const uint32_t sb16 = (sb & 0x3FFFFu) >> 4;
  float acc[F ? 48 : 80], acb[32];
  const int rot = (F && (nt & 1)) ? 1 : 0;
  const uint32_t lbo96 = (1024u + 4u * rot) << 16;
#define ACC(i) (F && (i) >= 48 ? acb[(i) >= 48 ? (i) - 48 : 0] : acc[F && (i) >= 48 ? 0 : (i)])
  PROF_EV(32 + wg * 8 + 0);
  mbar_wait(sb + B_FULL2, 0);
  p2_mma<F, true>(acc, acb, sb16 + wg * 512, sb16 + (CH >> 4), lbo96);
  int s = 1, ph = 0;
  float v[NCH] = {};
#define P2_STEP_WITH_PIECE(K)                                                                                    \
  if constexpr (NPRE + (K) < 8) {                                                                                \
    if (wg == 1) ffn_piece<true, (NPRE + (K)) & 7>(u0, u1, tile, w, lane, v, P.zero);                            \
    if (NPRE + (K) == 7 && wg == 1) bar_arrive(4, 160);                                                          \
    mbar_wait(sb + B_FULL2 + 8 * (((K) + 1) % 5), (((K) + 1) / 5) & 1);                                          \
    p2_mma<F, false>(acc, acb, sb16 + (((K) + 1) % 5) * (ST2 >> 4) + wg * 512,                                   \
                     sb16 + (((K) + 1) % 5) * (ST2 >> 4) + (CH >> 4), lbo96);                                    \
    wg_wait<1>();                                                                                                \
    mbar_arrive_elect(sb + B_EMPTY2 + 8 * ((K) % 5));                                                            \
  }
  P2_STEP_WITH_PIECE(0) P2_STEP_WITH_PIECE(1) P2_STEP_WITH_PIECE(2) P2_STEP_WITH_PIECE(3)
  P2_STEP_WITH_PIECE(4) P2_STEP_WITH_PIECE(5) P2_STEP_WITH_PIECE(6) P2_STEP_WITH_PIECE(7)
#undef P2_STEP_WITH_PIECE
  if (NPRE == 8 && wg == 1) bar_arrive(4, 160);
  s = (9 - NPRE) % 5;
  ph = ((9 - NPRE) / 5) & 1;
#pragma unroll 1
  for (int k = 9 - NPRE; k < NK; k++) {
    if (k == NK - 4 && wg == 1) {
      wg_wait<0>();
      if (elect_one()) mbar_arrive_remote(mapa(sb + B_PEER, peer));
      if (STAG) bar_sync(6, 256);
    }
    if (threadIdx.x == 128) TR(50 + k, 1);
    { PROF_T0; mbar_wait(sb + B_FULL2 + 8 * s, ph); PROF_ACC(pw); }
    if (threadIdx.x == 128) TR(50 + k, 2);
    p2_mma<F, false>(acc, acb, sb16 + s * (ST2 >> 4) + wg * 512, sb16 + s * (ST2 >> 4) + (CH >> 4), lbo96);
    wg_wait<1>();
    if (k < NK - 4) mbar_arrive_elect(sb + B_EMPTY2 + 8 * (s == 0 ? 4 : s - 1));
    else if (k == NK - 4 && wg == 0 && elect_one()) mbar_arrive_remote(mapa(sb + B_PEER, peer));
    if (++s == 5) { s = 0; ph ^= 1; }
  }
  if (STAG && wg == 0) bar_arrive(6, 256);
  const int lrow = 8 * (2 * wg + (w >> 1));
  const int tk = 64 * (w & 1) + (F ? 32 : 0) + lrow + r;
#define CB(n) (!F ? (n) : (n) < 2 ? (n) + rot : (n) == 2 ? 4 - 4 * rot : (n) - 1 + rot)
  constexpr int RSLOT = NK % 5, RSLOT_PEER = F ? (2 * NCG) % 5 : NFC % 5;
  const uint32_t rdst = mapa(sb + RSLOT_PEER * ST2 + warp * 2560 + lane * 16, peer);
  const uint32_t rbar = mapa(sb + B_RECV + 8 * warp, peer);
  const bool odd = q & 1;
  const uint32_t rsrc = sb + RSLOT * ST2 + warp * 2560 + (lane & ~1) * 16 + (odd ? 8 : 0);
  float* orow = P.out + (size_t)(rb * 128 + tk) * DM + 160 * nt + (odd ? 2 * q + 6 : 2 * q);
  constexpr int OS = F ? 0 : 2, OK = F ? 2 : 0;
  mbar_wait_cluster(sb + B_PEER, 0);
  wg_wait<0>();
  fence_regs(acc);
  if (F) fence_regs(acb);
  PROF_EV(32 + wg * 8 + 1);
#pragma unroll
  for (int n = 0; n < 5; n++) {
    uint32_t p[4];
#pragma unroll
    for (int i = 0; i < 4; i++) p[i] = pack_bf16(ACC(16 * n + 4 * i + OS), ACC(16 * n + 4 * i + OS + 1));
    asm volatile("st.async.weak.shared::cluster.mbarrier::complete_tx::bytes.v4.b32 [%0], {%1, %2, %3, %4}, [%5];"
                 ::"r"(rdst + CB(n) * 512), "r"(p[0]), "r"(p[2]), "r"(p[1]), "r"(p[3]), "r"(rbar) : "memory");
  }
  float g;
  uint32_t xd[20];
  mbar_wait(sb + B_G, 0);
  asm volatile("ld.shared.f32 %0, [%1];" : "=f"(g) : "r"(sb + SM_G + 4 * tk) : "memory");
  mbar_wait(sb + B_XS, 0);
  {
    const uint32_t xa = sb + SM_XS + (w & 1) * 10752 + (lrow + (lane & 7)) * 336 + (lane >> 3) * 16;
    const uint32_t da = sb + SM_XS + 21504 + (lane >> 3) * 16;
#pragma unroll
    for (int n = 0; n < 5; n++) {
      uint32_t xv[4], dv[4];
      ldmatrix4(xv, xa + CB(n) * 64);
      ldmatrix4(dv, da + CB(n) * 64);
#pragma unroll
      for (int i = 0; i < 4; i++) asm("mul.bf16x2 %0, %1, %2;" : "=r"(xd[4 * n + i]) : "r"(xv[i]), "r"(dv[i]));
    }
  }
  const float sk = F ? 1.0f - g : 2.0f * g, sr = F ? 2.0f * g : 1.0f - g;
  float o[40];
#pragma unroll
  for (int i = 0; i < 10; i++) {
    float a[2], b[2];
#pragma unroll
    for (int e = 0; e < 2; e++) {
      const float u0 = fmaf(ACC(8 * i + OK + e), sk, g * (e ? bf_hi(xd[2 * i]) : bf_lo(xd[2 * i])));
      const float u1 = fmaf(ACC(8 * i + 4 + OK + e), sk, g * (e ? bf_hi(xd[2 * i + 1]) : bf_lo(xd[2 * i + 1])));
      a[e] = odd ? u1 : u0;
      b[e] = __shfl_xor_sync(0xffffffffu, odd ? u0 : u1, 1);
    }
    o[4 * i] = odd ? b[0] : a[0]; o[4 * i + 1] = odd ? b[1] : a[1];
    o[4 * i + 2] = odd ? a[0] : b[0]; o[4 * i + 3] = odd ? a[1] : b[1];
  }
  fence_regs(o);
  mbar_wait_cluster(sb + B_RECV + 8 * warp, 0);
  PROF_EV(32 + wg * 8 + 2);
#pragma unroll
  for (int n = 0; n < 5; n++) {
    uint32_t lo[2], hi[2];
    asm volatile("ld.shared.v2.b32 {%0, %1}, [%2];" : "=r"(lo[0]), "=r"(lo[1]) : "r"(rsrc + CB(n) * 512) : "memory");
    asm volatile("ld.shared.v2.b32 {%0, %1}, [%2];" : "=r"(hi[0]), "=r"(hi[1]) : "r"(rsrc + CB(n) * 512 + 16) : "memory");
#pragma unroll
    for (int h = 0; h < 2; h++) {
      const int i = 2 * n + h;
      *(float4*)(orow + 32 * CB(n) + 16 * h) = make_float4(fmaf(bf_lo(lo[h]), sr, o[4 * i]), fmaf(bf_hi(lo[h]), sr, o[4 * i + 1]),
                                                           fmaf(bf_lo(hi[h]), sr, o[4 * i + 2]), fmaf(bf_hi(hi[h]), sr, o[4 * i + 3]));
    }
  }
  PROF_EV(32 + wg * 8 + 3);
#undef ACC
#undef CB
}

__global__ void __launch_bounds__(384, 1) __cluster_dims__(2, 1, 1) fused_kernel(const __grid_constant__ Params P) {
  extern __shared__ __align__(1024) unsigned char smem_raw[];
  const uint32_t sb = smem_u32(smem_raw);
  trap_if_over((int)(sb & 1023u), 0);
  const int warp = __shfl_sync(0xffffffffu, threadIdx.x >> 5, 0), lane = threadIdx.x & 31;
  if (warp == 10 && elect_one()) { prefetch_map(&P.x); prefetch_map(&P.wg); prefetch_map(&P.wu); }
  uint32_t ftype, smid;
  asm("mov.u32 %0, %%cluster_ctarank;" : "=r"(ftype));
  asm("mov.u32 %0, %%smid;" : "=r"(smid));
  const int tp = P.use_smid ? (int)(smid >> 1) : (int)(blockIdx.x >> 1);
  int gpc, idx;
  bool extra = false;
  if (tp < 32) { gpc = tp & 7; idx = tp >> 3; }
  else if (tp < 60) { gpc = 1 + (tp - 32) % 7; idx = 4 + (tp - 32) / 7; }
  else if (tp < 62) { gpc = 0; idx = tp - 60; extra = true; }
  else { gpc = 0; idx = tp - 58; }
  const int rb = extra ? (idx * 2 + ftype) * 4 : MAP == 0 ? 2 * gpc + (idx >> 2) : MAP == 1 ? 4 * (gpc >> 1) + (idx & 3) : 8 * (gpc >> 2) + idx;
  const int nt = MAP == 0 ? idx & 3 : MAP == 1 ? 2 * (gpc & 1) + (idx >> 2) : gpc & 3;
  const int role = tp * 2 + ftype;
  const int nslots = (extra || ftype) ? 4 : 5;

  if (warp == 8) PROF_EV(58);
  if (warp == 8) {
    if (elect_one()) {
#pragma unroll
      for (int i = 0; i < 18; i++) mbar_init(sb + SM_BAR + 8 * i, i < 14 ? 1 : 4);
      asm volatile("fence.mbarrier_init.release.cluster;" ::: "memory");
    }
    __syncwarp();
    bar_arrive(0, 384);
    PROF_EV(56);
    const int fc0 = extra ? EXTRA_FC : ftype * 4 + nt;
#pragma unroll 1
    for (int k = 0; k < 4; k++) {
      const uint32_t res = sb + SM_RES + k * CH, ring = sb + SM_RING + k * CH;
      const uint32_t bx = sb + B_XFULL + 8 * k, bf = sb + B_FULL1 + 8 * k;
      if (elect_one()) {
        mbar_expect_tx(bx, extra && k == 0 ? CH + 1280 : CH);
        mbar_expect_tx(bf, CH);
        tma5d(extra ? ring : res, &P.x, 64 * k, rb, extra ? bf : bx);
        tma2d(extra ? res : ring, &P.wg, 64 * fc0, 64 * k, extra ? bx : bf);
        tma2d((extra ? res : ring) + 8192, &P.wu, 64 * fc0, 64 * k, extra ? bx : bf);
        if (extra && k == 0) bulk_load(sb + SM_GW, P.gatew, 1280, bx);
      }
      if (k == 0) PROF_EV(57);
    }
  } else {
    if (warp == 9 && elect_one()) {
#pragma unroll
      for (int i = 18; i < 40; i++) mbar_init(sb + SM_BAR + 8 * i, i < 23 ? 1 : i < 28 ? 8 : i == 28 ? 32 : i == 29 ? 8 : i == 39 ? 128 : 1);
      asm volatile("st.shared.u32 [%0], %1;" ::"r"(sb + SM_READY), "r"(0) : "memory");
      asm volatile("fence.mbarrier_init.release.cluster;" ::: "memory");
    }
    __syncwarp();
    bar_sync(0, 384);
  }
  asm volatile("barrier.cluster.arrive.relaxed.aligned;" ::: "memory");

  if (warp >= 8) {
    asm volatile("setmaxnreg.dec.sync.aligned.u32 40;");
    if (warp == 8) {
      int it = 4;
#pragma unroll 1
      for (int slot = 0; slot < nslots; slot++) {
        bool ssm = false;
        const int id = extra ? 0 : unit_of(ftype, nt, slot, ssm);
        const CUtensorMap* m0 = ssm ? &P.bre : &P.wg;
        const int c0 = ssm ? 0 : 64 * id, c1 = ssm ? 64 * id : 0, d0 = ssm ? 64 : 0;
#pragma unroll 1
        for (int k = slot == 0 ? 4 : 0; k < 10; k++, it++) {
          const int s = it & 3;
          const uint32_t ring = sb + SM_RING + s * CH, bf = sb + B_FULL1 + 8 * s;
          if (slot == 0 && elect_one()) {
            const uint32_t res = sb + SM_RES + k * CH, bx = sb + B_XFULL + 8 * k;
            mbar_expect_tx(bx, CH);
            if (!extra) tma5d(res, &P.x, 64 * k, rb, bx);
            else { tma2d(res, &P.wg, 64 * EXTRA_FC, 64 * k, bx); tma2d(res + 8192, &P.wu, 64 * EXTRA_FC, 64 * k, bx); }
          }
          { PROF_T0; mbar_wait(sb + B_EMPTY1 + 8 * s, ((it >> 2) & 1) ^ 1); PROF_ACC(pw1); }
          TR(it, 0);
          if (elect_one()) {
            mbar_expect_tx(bf, CH);
            if (extra) tma5d(ring, &P.x, 64 * k, rb + slot, bf);
            else {
              tma2d(ring, m0, c0 + d0 * k, c1 + (64 - d0) * k, bf);
              tma2d(ring + 8192, m0 + 1, c0 + d0 * k, c1 + (64 - d0) * k, bf);
            }
          }
        }
      }
      if (!extra) {
        const int nk = ftype ? NFC : 2 * NCG;
        const int dc = 160 * nt + ((nt & 1) ? 32 : 0);
        const unsigned char* asrc = P.scr + (ftype ? G_ACT + (size_t)(rb * NFC) * CH : G_H + (size_t)(rb * 2 * NCG) * CH);
        int s = 0, ph = 1;
        uint32_t ready = 0;
#pragma unroll 1
        for (int k2 = 0; k2 < nk; k2++) {
          if (k2 >= 5) {
            PROF_T0; mbar_wait(sb + B_EMPTY2 + 8 * s, ph); PROF_ACC(pw2);
          } else if (k2 == 2 || k2 == 3) {
            mbar_wait(sb + B_EMPTY1 + 8 * (it & 3), ((it >> 2) & 1) ^ 1);
            it++;
            mbar_wait(sb + B_EMPTY1 + 8 * (it & 3), ((it >> 2) & 1) ^ 1);
            it++;
          }
          TR(50 + k2, 0);
          const uint32_t st = sb + s * ST2, bf = sb + B_FULL2 + 8 * s;
          if (elect_one()) {
            if (ftype) {
              mbar_expect_tx(bf, 40960);
              tma5d(st + CH, &P.wd, dc, 2 * k2, bf);
              tma5d(st + CH + 8192, &P.wd, dc + 64, 2 * k2, bf);
              tma5d(st + CH + 16384, &P.wd, 128 + 320 * (nt >> 1), 2 * k2, bf);
            } else {
              mbar_expect_tx(bf, 36864);
              tma2d(st + CH, &P.cre + (k2 & 1), 64 * (k2 >> 1), 160 * nt, bf);
            }
          }
          const uint32_t need = ftype ? k2 : k2 >> 1;
          if (ready <= need) {
            int spin = 0;
            PROF_T0;
            do {
              asm volatile("ld.acquire.cta.shared.u32 %0, [%1];" : "=r"(ready) : "r"(sb + SM_READY) : "memory");
              trap_if_over(++spin, 1 << 26);
            } while (ready <= need);
            asm volatile("fence.proxy.async.global;" ::: "memory");
            PROF_ACC(pw3);
          }
          if (elect_one()) {
            bulk_load(st, asrc + (size_t)k2 * CH, CH, bf);
            if (k2 == XSK) {
              mbar_expect_tx(sb + B_XS, 21824);
              tma2d(sb + SM_XS, &P.xs, 160 * nt, rb * 128 + 32 * ftype, sb + B_XS);
              tma2d(sb + SM_XS + 10752, &P.xs, 160 * nt, rb * 128 + 64 + 32 * ftype, sb + B_XS);
              bulk_load(sb + SM_XS + 21504, P.dskip + 160 * nt, 320, sb + B_XS);
            }
          }
          if (++s == 5) { s = 0; ph ^= 1; }
        }
      }
    } else if (warp == 9) {
      const unsigned want = load_epoch(P, role) + 1;
      if (elect_one()) {
        prefetch_map(&P.bre); prefetch_map(&P.bim);
        if (ftype) prefetch_map(&P.wd); else { prefetch_map(&P.cre); prefetch_map(&P.cim); }
        prefetch_map(&P.xs);
      }
      for (int slot = 0; slot < nslots; slot++) {
        bool ssm = false;
        const int id = extra ? EXTRA_FC : unit_of(ftype, nt, slot, ssm);
        bar_sync(3 + ((slot + nslots) & 1), 160);
        if (elect_one()) {
          asm volatile("fence.acq_rel.gpu;" ::: "memory");
          asm volatile("st.relaxed.gpu.global.u32 [%0], %1;" ::"l"(P.scr + (ssm ? G_FLAG_H : G_FLAG_ACT) + 4 * ((extra ? rb + slot : rb) * 32 + id)), "r"(want) : "memory");
        }
        __syncwarp();
      }
      if (extra && lane == 0) asm volatile("red.relaxed.gpu.global.add.u32 [%0], 1;" ::"l"(P.scr + G_EPOCH + 4 * role) : "memory");
    } else if (warp == 10 && !extra) {
      const unsigned want = load_epoch(P, role) + 1;
      const int nf = ftype ? NFC : NCG;
      const unsigned char* fl = P.scr + (lane == 31 ? G_FLAG_ACT + 4 * EXTRA_FC : (ftype ? G_FLAG_ACT : G_FLAG_H) + 4 * lane) + 128 * rb;
      mbar_wait(sb + B_XFULL + 8 * 9, 0);
      __nanosleep(4000);
      uint32_t last = 0;
      int spin = 0;
      while (last < 32) {
        unsigned v = want;
        if (lane < nf || lane == 31) asm volatile("ld.acquire.gpu.global.u32 %0, [%1];" : "=r"(v) : "l"(fl) : "memory");
        const unsigned miss = __ballot_sync(0xffffffffu, v != want);
        const uint32_t n = miss ? __ffs(miss) - 1 : 32;
        __syncwarp();
        if (n > last) {
          last = n;
          if (lane == 0) asm volatile("st.release.cta.shared.u32 [%0], %1;" ::"r"(sb + SM_READY), "r"(n) : "memory");
        } else {
          __nanosleep(200);
        }
        trap_if_over(++spin, 1 << 22);
      }
      float4 gv;
      asm volatile("ld.relaxed.gpu.global.v4.f32 {%0, %1, %2, %3}, [%4];" : "=f"(gv.x), "=f"(gv.y), "=f"(gv.z), "=f"(gv.w) : "l"(P.scr + G_GATE + rb * 512 + 16 * lane) : "memory");
      asm volatile("st.shared.v4.f32 [%0], {%1, %2, %3, %4};" ::"r"(sb + SM_G + 16 * lane), "f"(gv.x), "f"(gv.y), "f"(gv.z), "f"(gv.w) : "memory");
      mbar_arrive(sb + B_G);
      if (lane == 0) asm volatile("red.relaxed.gpu.global.add.u32 [%0], 1;" ::"l"(P.scr + G_EPOCH + 4 * role) : "memory");
    } else if (warp == 11 && !extra) {
      const int pc = (rb * 4 + nt) * 2 + ftype;
      const char* wrow = (lane & 1 ? P.p_wu : P.p_wg) + (size_t)(pc * 5 + (lane >> 1)) * (FF * 2);
      mbar_wait(sb + B_XFULL + 8 * PF0, 0);
      if (lane < 2) l2_prefetch((lane ? P.p_bim : P.p_bre) + pc * 5120, 5120);
      mbar_wait(sb + B_XFULL + 8 * 9, 0);
      if (lane < 10) l2_prefetch(wrow + 8 * 128, 6 * 128);
      if (lane < 2) l2_prefetch((lane ? P.p_bim : P.p_bre) + 655360 + pc * 1280, 1280);
      __nanosleep(PFD);
      if (lane < 10) l2_prefetch(wrow + 14 * 128, 8 * 128);
      __nanosleep(PFD / 2);
      if (lane == 0) l2_prefetch(P.p_wd + pc * 8640, 8640);
      __nanosleep(PFD / 2);
      if (lane < 10) l2_prefetch(wrow + 23 * 128, 4 * 128);
      if (lane == 0) l2_prefetch(P.p_wd + 1105920 + pc * 8640, 8640);
      __nanosleep(PFD / 2);
      if (lane < 2) l2_prefetch((lane ? P.p_cim : P.p_cre) + pc * 6400, 6400);
    }
    __syncwarp();
    asm volatile("barrier.cluster.wait.acquire.aligned;" ::: "memory");
  } else {
    const int wg = warp >> 2, w = warp & 3;
    if (((wg + nslots) & 1) != 0) mbar_wait(sb + B_XFULL, 0);
    asm volatile("setmaxnreg.inc.sync.aligned.u32 232;");
    if (extra) {
#pragma unroll 1
      for (int slot = wg; slot < 4; slot += 2) {
        float acc0[64], acc1[64], g0[4], g1[4];
        if (slot > 0) bar_sync(1 + wg, 256);
        PROF_EV(slot * 4 + 0);
        const float tok = unit_mainloop<2>(acc0, acc1, g0, g1, sb, slot * 10, slot < 2, slot < 3, wg, lane PROF_ARGS);
        PROF_EV(slot * 4 + 1);
        if ((lane & 3) == 0) {
#pragma unroll
          for (int i = 0; i < 4; i++) {
            const int c = 64 * (i >> 1) + 16 * w + 8 * (i & 1) + (lane >> 2);
            const float z = (i >> 1) ? g1[2 * (i & 1)] : g0[2 * (i & 1)];
            ((float*)(P.scr + G_GATE))[(rb + slot) * 128 + 32 * ((c >> 1) & 3) + 2 * (c >> 3) + (c & 1)] = 1.0f / (1.0f + expf(-z));
          }
        }
        unsigned char* tile = P.scr + G_ACT + (size_t)((rb + slot) * NFC + EXTRA_FC) * CH;
        float v[NCH];
#pragma unroll
        for (int i = 0; i < NCH; i++) v[i] = tok;
        ffn_pieces<true, 8>(acc0, acc1, tile, w, lane, v, P.zero);
        PROF_EV(slot * 4 + 2);
        bar_arrive(3 + wg, 160);
      }
      asm volatile("barrier.cluster.wait.acquire.aligned;" ::: "memory");
    } else {
#pragma unroll 1
      for (int slot = (wg + nslots) & 1; slot < nslots - 1; slot += 2) {
        bool ssm = false;
        const int id = unit_of(ftype, nt, slot, ssm);
        const bool signal = true;
        float acc0[64], acc1[64], g0[4], g1[4];
        if (ssm) {
          const unsigned tag = load_epoch(P, role);
          if (slot == 1) {
            const int t = threadIdx.x & 127;
            const float4 cf = ssm_coef(P, t < 64 ? 64 * id + t : 512 + 64 * (nt & 1) + t - 64);
            asm volatile("st.shared.v4.f32 [%0], {%1, %2, %3, %4};" ::"r"(sb + SM_GW + 16 * t), "f"(cf.x), "f"(cf.y), "f"(cf.z), "f"(cf.w) : "memory");
            mbar_arrive(sb + B_COEF);
          }
          mbar_wait(sb + B_COEF, 0);
          SsmCoef co[2];
          co[0] = ssm_powers(sb + SM_GW + (slot - 1) * 1024 + 16 * (16 * w + (lane >> 2)));
          co[1] = ssm_powers(sb + SM_GW + (slot - 1) * 1024 + 16 * (16 * w + (lane >> 2) + 8));
          bar_sync(1 + wg, 256);
          PROF_EV(slot * 4 + 0);
          const float tok = unit_mainloop<1>(acc0, acc1, g0, g1, sb, slot * 10, slot < 2, signal, wg, lane PROF_ARGS);
          PROF_EV(slot * 4 + 1);
          ssm_epilogue(acc0, acc1, co, P.scr, rb, id, tag + 1, w, lane, P.zero, tok);
        } else {
          if (slot > 0) bar_sync(1 + wg, 256);
          PROF_EV(slot * 4 + 0);
          const float tok = unit_mainloop<0>(acc0, acc1, g0, g1, sb, slot * 10, slot < 2, signal, wg, lane PROF_ARGS);
          PROF_EV(slot * 4 + 1);
          unsigned char* tile = P.scr + G_ACT + (size_t)(rb * NFC + id) * CH;
          float v[NCH];
#pragma unroll
          for (int i = 0; i < NCH; i++) v[i] = tok;
          ffn_pieces<true, 8>(acc0, acc1, tile, w, lane, v, P.zero);
        }
        PROF_EV(slot * 4 + 2);
        bar_arrive(3 + wg, 160);
      }
      float acc0[64], acc1[64], g0[4], g1[4];
      unsigned char* tile = P.scr + G_ACT + (size_t)(rb * NFC + (ftype ? 18 : 23) + nt) * CH;
      if (wg == 1) {
        const int slot = nslots - 1;
        bar_sync(2, 256);
        PROF_EV(slot * 4 + 0);
        const float tok = unit_mainloop<0>(acc0, acc1, g0, g1, sb, slot * 10, false, false, 1, lane PROF_ARGS);
        PROF_EV(slot * 4 + 1);
        float v[NCH];
        v[0] = chain(-1.4426950408889634f, tok, P.zero);
        ffn_pieces<false, NPRE>(acc0, acc1, tile, w, lane, v, P.zero);
        PROF_EV(slot * 4 + 2);
      }
      if (ftype) phase2<true>(P, sb, rb, nt, wg, w, lane, acc0, acc1, tile PROF_ARGS);
      else phase2<false>(P, sb, rb, nt, wg, w, lane, acc0, acc1, tile PROF_ARGS);
    }
  }
}

typedef CUresult (*EncodeFn)(CUtensorMap*, CUtensorMapDataType, cuuint32_t, void*, const cuuint64_t*, const cuuint64_t*,
                             const cuuint32_t*, const cuuint32_t*, CUtensorMapInterleave, CUtensorMapSwizzle,
                             CUtensorMapL2promotion, CUtensorMapFloatOOBfill);

void encode(EncodeFn fn, CUtensorMap* m, const void* base, int rank, const cuuint64_t* dims, const cuuint64_t* strides,
            const cuuint32_t* box, CUtensorMapSwizzle swz = CU_TENSOR_MAP_SWIZZLE_128B) {
  const cuuint32_t es[5] = {1, 1, 1, 1, 1};
  fn(m, CU_TENSOR_MAP_DATA_TYPE_BFLOAT16, rank, const_cast<void*>(base), dims, strides, box, es,
     CU_TENSOR_MAP_INTERLEAVE_NONE, swz, CU_TENSOR_MAP_L2_PROMOTION_L2_128B,
     CU_TENSOR_MAP_FLOAT_OOB_FILL_NONE);
}

}

extern "C" void kernel_launch(void* const* d_in, const int* in_sizes, int n_in, void* d_out, int out_size) {
  (void)in_sizes; (void)n_in; (void)out_size;
  static EncodeFn enc = nullptr;
  static int sms = 0;
  static void* scratch = nullptr;
  if (!enc) {
    void* fn = nullptr;
    cudaDriverEntryPointQueryResult qr;
    cudaGetDriverEntryPoint("cuTensorMapEncodeTiled", &fn, cudaEnableDefault, &qr);
    enc = (EncodeFn)fn;
    int dev = 0;
    cudaGetDevice(&dev);
    cudaDeviceGetAttribute(&sms, cudaDevAttrMultiProcessorCount, dev);
    cudaGetSymbolAddress(&scratch, g_scratch);
    cudaFuncSetAttribute(fused_kernel, cudaFuncAttributeMaxDynamicSharedMemorySize, SMEM_BYTES);
  }
  typedef const __nv_bfloat16* bp;
  Params P;
  const cuuint64_t R = DM * 2;
  {
    const cuuint64_t d[5] = {DM, 2, 4, 16, NRB}, s[4] = {R, 32 * R, 2 * R, 128 * R};
    const cuuint32_t b[5] = {64, 2, 4, 16, 1};
    encode(enc, &P.x, d_in[0], 5, d, s, b);
  }
  {
    const cuuint64_t d[2] = {DM, DM}, s[1] = {R};
    const cuuint32_t b[2] = {64, 64}, bc[2] = {64, 160};
    encode(enc, &P.bre, d_in[3], 2, d, s, b);
    encode(enc, &P.bim, d_in[4], 2, d, s, b);
    encode(enc, &P.cre, d_in[5], 2, d, s, bc);
    encode(enc, &P.cim, d_in[6], 2, d, s, bc);
  }
  {
    const cuuint64_t d[2] = {FF, DM}, s[1] = {FF * 2};
    const cuuint32_t b[2] = {64, 64};
    encode(enc, &P.wg, d_in[10], 2, d, s, b);
    encode(enc, &P.wu, d_in[11], 2, d, s, b);
  }
  {
    cuuint64_t d[5] = {DM, 2, 4, 4, FF / 32};
    const cuuint64_t s[4] = {R, 8 * R, 2 * R, 32 * R};
    const cuuint32_t b[5] = {64, 2, 4, 4, 2};
    encode(enc, &P.wd, d_in[12], 5, d, s, b);
  }
  {
    const cuuint64_t d[2] = {DM, 2048}, s[1] = {R};
    const cuuint32_t b[2] = {168, 32};
    encode(enc, &P.xs, d_in[0], 2, d, s, b, CU_TENSOR_MAP_SWIZZLE_NONE);
  }
  P.scr = (unsigned char*)scratch;
  P.lre = (bp)d_in[1]; P.lim = (bp)d_in[2]; P.logdt = (bp)d_in[7]; P.dskip = (bp)d_in[8];
  P.gatew = (bp)d_in[13];
  P.p_bre = (const char*)d_in[3]; P.p_bim = (const char*)d_in[4]; P.p_cre = (const char*)d_in[5]; P.p_cim = (const char*)d_in[6];
  P.p_wg = (const char*)d_in[10]; P.p_wu = (const char*)d_in[11]; P.p_wd = (const char*)d_in[12];
  P.out = (float*)d_out;
  P.use_smid = sms == 132;
  P.zero = 0;
  fused_kernel<<<132, 384, SMEM_BYTES, cudaStreamPerThread>>>(P);
}
```

```cpp
#include <cuda_runtime.h>
#include <cuda_bf16.h>
#include <cuda.h>
#include <stdint.h>

#define RELH 0
#define PF0 9
#define PFD 2400
#define P1DENSE 0
#define NCH 3
#define GATHER_AT 40
#define PMCH 1
#define P2DENSE 0
#define STAG 1
#define XSK 4
#define NPRE 4
#define SF 1
#define MAP 1
#define EPF 0
namespace {

constexpr int DM = 640, FF = 1728;
constexpr int NRB = 16;
constexpr int NFC = 27;
constexpr int NCG = 10;
constexpr int CH = 16384;
constexpr int EXTRA_FC = 22;

constexpr int SM_RES = 0;
constexpr int SM_RING = 10 * CH;
constexpr int ST2 = 40960;
constexpr int SM_XS = 5 * ST2;
constexpr int SM_BAR = 14 * CH;
constexpr int B_XFULL = SM_BAR;
constexpr int B_FULL1 = B_XFULL + 80;
constexpr int B_EMPTY1 = B_FULL1 + 32;
constexpr int B_FULL2 = B_EMPTY1 + 32;
constexpr int B_EMPTY2 = B_FULL2 + 40;
constexpr int B_G = B_EMPTY2 + 40;
constexpr int B_PEER = B_G + 8;
constexpr int B_RECV = B_PEER + 8;
constexpr int B_XS = B_RECV + 64;
constexpr int B_COEF = B_XS + 8;
constexpr int SM_READY = B_COEF + 8;
constexpr int SM_G = SM_BAR + 512;
constexpr int SM_GW = SM_BAR + 1024;
constexpr int SMEM_BYTES = SM_GW + 2048;

constexpr size_t G_EPOCH = 0;
constexpr size_t G_FLAG_ACT = 1024;
constexpr size_t G_FLAG_H = G_FLAG_ACT + 2048;
constexpr size_t G_GATE = G_FLAG_H + 2048;
constexpr size_t G_AGG = G_GATE + 8192;
constexpr size_t G_H = G_AGG + NCG * NRB * 64 * 16 + 3072;
constexpr size_t G_ACT = G_H + (size_t)NRB * NCG * 2 * CH;
static_assert(G_H % 1024 == 0, "tile alignment");
__device__ __align__(1024) unsigned char g_scratch[G_ACT + (size_t)NRB * NFC * CH];

struct Params {
  const char *p_x, *p_wg, *p_wu;
  unsigned char* scr;
  float* out;
  uint32_t zero;
  const __nv_bfloat16 *lre, *lim, *logdt, *dskip, *gatew;
  const char *p_cre, *p_cim, *p_wd, *p_bre, *p_bim;
  CUtensorMap x, wg, wu, bre, bim, cre, cim, wd, xs;
};

#define PROF_EV(i)
#define TR(it, f)
#define PROF_ARGS
#define PROF_T0
#define PROF_ACC(v)

__device__ __forceinline__ uint32_t smem_u32(const void* p) { return (uint32_t)__cvta_generic_to_shared(p); }
__device__ __forceinline__ bool elect_one() {
  uint32_t p;
  asm volatile("{\n.reg .pred p;\nelect.sync _|p, 0xffffffff;\nselp.u32 %0, 1, 0, p;\n}" : "=r"(p));
  return p != 0;
}
__device__ __forceinline__ void mbar_init(uint32_t bar, uint32_t cnt) {
  asm volatile("mbarrier.init.shared::cta.b64 [%0], %1;" ::"r"(bar), "r"(cnt) : "memory");
}
__device__ __forceinline__ void mbar_expect_tx(uint32_t bar, uint32_t bytes) {
  asm volatile("mbarrier.arrive.expect_tx.shared::cta.b64 _, [%0], %1;" ::"r"(bar), "r"(bytes) : "memory");
}
__device__ __forceinline__ void mbar_arrive(uint32_t bar) {
  asm volatile("mbarrier.arrive.shared::cta.b64 _, [%0];" ::"r"(bar) : "memory");
}
__device__ __forceinline__ uint32_t mapa(uint32_t addr, uint32_t cta) {
  uint32_t r;
  asm("mapa.shared::cluster.u32 %0, %1, %2;" : "=r"(r) : "r"(addr), "r"(cta));
  return r;
}
__device__ __forceinline__ void mbar_arrive_remote(uint32_t cluster_bar) {
  asm volatile("mbarrier.arrive.relaxed.cluster.shared::cluster.b64 _, [%0];" ::"r"(cluster_bar) : "memory");
}
__device__ __forceinline__ void mbar_wait(uint32_t bar, uint32_t parity) {
  asm volatile("{\n.reg .pred p;\n.reg .u32 c;\nmov.u32 c, 0;\n"
               "W:\nmbarrier.try_wait.parity.shared::cta.b64 p, [%0], %1;\n@p bra D;\n"
               "add.u32 c, c, 1;\nsetp.gt.u32 p, c, 1048576;\n@p trap;\nbra W;\nD:\n}"
               ::"r"(bar), "r"(parity) : "memory");
}
__device__ __forceinline__ void mbar_wait_cluster(uint32_t bar, uint32_t parity) {
  asm volatile("{\n.reg .pred p;\n.reg .u32 c;\nmov.u32 c, 0;\n"
               "W:\nmbarrier.try_wait.parity.acquire.cluster.shared::cta.b64 p, [%0], %1;\n@p bra D;\n"
               "add.u32 c, c, 1;\nsetp.gt.u32 p, c, 1048576;\n@p trap;\nbra W;\nD:\n}"
               ::"r"(bar), "r"(parity) : "memory");
}
__device__ __forceinline__ uint32_t mbar_test(uint32_t bar, uint32_t parity) {
  uint32_t ok;
  asm volatile("{\n.reg .pred p;\nmbarrier.test_wait.parity.shared::cta.b64 p, [%1], %2;\nselp.u32 %0, 1, 0, p;\n}"
               : "=r"(ok) : "r"(bar), "r"(parity) : "memory");
  return ok;
}
__device__ __forceinline__ void mbar_arrive_elect(uint32_t bar) {
  asm volatile("{\n.reg .pred p;\nelect.sync _|p, 0xffffffff;\n@p mbarrier.arrive.shared::cta.b64 _, [%0];\n}" ::"r"(bar) : "memory");
}
__device__ __forceinline__ float mbar_arrive_token(uint32_t bar) {
  uint32_t lo;
  asm volatile("{\n.reg .pred p;\n.reg .b64 st;\n.reg .b32 hi;\nmov.b64 st, 0;\nelect.sync _|p, 0xffffffff;\n"
               "@p mbarrier.arrive.shared::cta.b64 st, [%1];\nmov.b64 {%0, hi}, st;\n}" : "=r"(lo) : "r"(bar) : "memory");
  return __uint_as_float(lo);
}
__device__ __forceinline__ void trap_if_over(int n, int limit) {
  asm volatile("{\n.reg .pred p;\nsetp.gt.s32 p, %0, %1;\n@p trap;\n}" ::"r"(n), "r"(limit));
}
__device__ __forceinline__ void bulk_load(uint32_t dst, const void* src, uint32_t bytes, uint32_t bar) {
  asm volatile("cp.async.bulk.shared::cluster.global.mbarrier::complete_tx::bytes [%0], [%1], %2, [%3];"
               ::"r"(dst), "l"(src), "r"(bytes), "r"(bar) : "memory");
}
__device__ __forceinline__ void tma2d(uint32_t dst, const CUtensorMap* m, int c0, int c1, uint32_t bar) {
  asm volatile("cp.async.bulk.tensor.2d.shared::cluster.global.mbarrier::complete_tx::bytes [%0], [%1, {%3, %4}], [%2];"
               ::"r"(dst), "l"(m), "r"(bar), "r"(c0), "r"(c1) : "memory");
}
__device__ __forceinline__ void tma5d(uint32_t dst, const CUtensorMap* m, int c0, int c4, uint32_t bar) {
  asm volatile("cp.async.bulk.tensor.5d.shared::cluster.global.mbarrier::complete_tx::bytes [%0], [%1, {%3, %5, %5, %5, %4}], [%2];"
               ::"r"(dst), "l"(m), "r"(bar), "r"(c0), "r"(c4), "r"(0) : "memory");
}
__device__ __forceinline__ void l2_prefetch(const void* p, uint32_t bytes) {
  asm volatile("cp.async.bulk.prefetch.L2.global [%0], %1;" ::"l"(p), "r"(bytes) : "memory");
}
__device__ __forceinline__ void prefetch_map(const CUtensorMap* m) {
  asm volatile("prefetch.tensormap [%0];" ::"l"(m) : "memory");
}
__device__ __forceinline__ void wg_fence() { asm volatile("wgmma.fence.sync.aligned;" ::: "memory"); }
__device__ __forceinline__ void wg_commit() { asm volatile("wgmma.commit_group.sync.aligned;" ::: "memory"); }
template <int N> __device__ __forceinline__ void wg_wait() { asm volatile("wgmma.wait_group.sync.aligned %0;" ::"n"(N) : "memory"); }
template <int R> __device__ __forceinline__ void fence_regs(float (&d)[R]) {
#pragma unroll
  for (int i = 0; i < R; i++) asm volatile("" : "+f"(d[i])::"memory");
}
__device__ __forceinline__ uint64_t desc_k(uint32_t a16) { return ((uint64_t)0x40000040u << 32) | (uint64_t)(a16 + (1u << 16)); }
__device__ __forceinline__ uint64_t desc_mn(uint32_t a16) { return ((uint64_t)0x40000040u << 32) | (uint64_t)(a16 + (512u << 16)); }
__device__ __forceinline__ void bar_sync(int id, int n) { asm volatile("bar.sync %0, %1;" ::"r"(id), "r"(n) : "memory"); }
__device__ __forceinline__ void bar_arrive(int id, int n) { asm volatile("bar.arrive %0, %1;" ::"r"(id), "r"(n) : "memory"); }
__device__ __forceinline__ uint32_t pack_bf16(float lo, float hi) {
  uint32_t r;
  asm("cvt.rn.bf16x2.f32 %0, %1, %2;" : "=r"(r) : "f"(hi), "f"(lo));
  return r;
}
__device__ __forceinline__ float bf_lo(uint32_t v) { return __uint_as_float(v << 16); }
__device__ __forceinline__ float bf_hi(uint32_t v) { return __uint_as_float(v & 0xFFFF0000u); }
__device__ __forceinline__ void st_v4(void* p, uint32_t a, uint32_t b, uint32_t c, uint32_t d) {
  asm volatile("st.global.v4.b32 [%0], {%1, %2, %3, %4};" ::"l"(p), "r"(a), "r"(b), "r"(c), "r"(d) : "memory");
}
__device__ __forceinline__ float fast_ex2(float x) { float y; asm("ex2.approx.ftz.f32 %0, %1;" : "=f"(y) : "f"(x)); return y; }
__device__ __forceinline__ float fast_rcp(float x) { float y; asm("rcp.approx.ftz.f32 %0, %1;" : "=f"(y) : "f"(x)); return y; }
struct cplx { float r, i; };
__device__ __forceinline__ cplx cmul(cplx a, cplx b) { return {a.r * b.r - a.i * b.i, a.r * b.i + a.i * b.r}; }
__device__ __forceinline__ cplx cfma(cplx a, cplx b, cplx c) {
  return {fmaf(a.r, b.r, fmaf(-a.i, b.i, c.r)), fmaf(a.r, b.i, fmaf(a.i, b.r, c.i))};
}
__device__ __forceinline__ cplx cshfl_up(cplx a, int d) {
  return {__shfl_up_sync(0xffffffffu, a.r, d, 4), __shfl_up_sync(0xffffffffu, a.i, d, 4)};
}

template <int TA, int TB>
__device__ __forceinline__ void wgmma_n8(float (&d)[4], uint64_t da, uint64_t db, int scale_d) {
  asm volatile("{\n.reg .pred p;\nsetp.ne.b32 p, %6, 0;\n"
    "wgmma.mma_async.sync.aligned.m64n8k16.f32.bf16.bf16 {"
    "%0, %1, %2, %3"
    "}, %4, %5, p, 1, 1, %7, %8;\n}\n"
    : "+f"(d[0]), "+f"(d[1]), "+f"(d[2]), "+f"(d[3])
    : "l"(da), "l"(db), "r"(scale_d), "n"(TA), "n"(TB));
}
template <int TA, int TB>
__device__ __forceinline__ void wgmma_n8_z(float (&d)[4], uint64_t da, uint64_t db) {
  asm volatile("{\n.reg .pred p;\nsetp.ne.b32 p, 0, 0;\n"
    "wgmma.mma_async.sync.aligned.m64n8k16.f32.bf16.bf16 {"
    "%0, %1, %2, %3"
    "}, %4, %5, p, 1, 1, %6, %7;\n}\n"
    : "=f"(d[0]), "=f"(d[1]), "=f"(d[2]), "=f"(d[3])
    : "l"(da), "l"(db), "n"(TA), "n"(TB));
}

template <int TA, int TB>
__device__ __forceinline__ void wgmma_n64(float (&d)[32], uint64_t da, uint64_t db, int scale_d) {
  asm volatile("{\n.reg .pred p;\nsetp.ne.b32 p, %34, 0;\n"
    "wgmma.mma_async.sync.aligned.m64n64k16.f32.bf16.bf16 {"
    "%0, %1, %2, %3, %4, %5, %6, %7, %8, %9, %10, %11, %12, %13, %14, %15, "
    "%16, %17, %18, %19, %20, %21, %22, %23, %24, %25, %26, %27, %28, %29, %30, %31"
    "}, %32, %33, p, 1, 1, %35, %36;\n}\n"
    : "+f"(d[0]), "+f"(d[1]), "+f"(d[2]), "+f"(d[3]), "+f"(d[4]), "+f"(d[5]), "+f"(d[6]), "+f"(d[7]),
      "+f"(d[8]), "+f"(d[9]), "+f"(d[10]), "+f"(d[11]), "+f"(d[12]), "+f"(d[13]), "+f"(d[14]), "+f"(d[15]),
      "+f"(d[16]), "+f"(d[17]), "+f"(d[18]), "+f"(d[19]), "+f"(d[20]), "+f"(d[21]), "+f"(d[22]), "+f"(d[23]),
      "+f"(d[24]), "+f"(d[25]), "+f"(d[26]), "+f"(d[27]), "+f"(d[28]), "+f"(d[29]), "+f"(d[30]), "+f"(d[31])
    : "l"(da), "l"(db), "r"(scale_d), "n"(TA), "n"(TB));
}
template <int TA, int TB>
__device__ __forceinline__ void wgmma_n64_z(float (&d)[32], uint64_t da, uint64_t db) {
  asm volatile("{\n.reg .pred p;\nsetp.ne.b32 p, 0, 0;\n"
    "wgmma.mma_async.sync.aligned.m64n64k16.f32.bf16.bf16 {"
    "%0, %1, %2, %3, %4, %5, %6, %7, %8, %9, %10, %11, %12, %13, %14, %15, "
    "%16, %17, %18, %19, %20, %21, %22, %23, %24, %25, %26, %27, %28, %29, %30, %31"
    "}, %32, %33, p, 1, 1, %34, %35;\n}\n"
    : "=f"(d[0]), "=f"(d[1]), "=f"(d[2]), "=f"(d[3]), "=f"(d[4]), "=f"(d[5]), "=f"(d[6]), "=f"(d[7]),
      "=f"(d[8]), "=f"(d[9]), "=f"(d[10]), "=f"(d[11]), "=f"(d[12]), "=f"(d[13]), "=f"(d[14]), "=f"(d[15]),
      "=f"(d[16]), "=f"(d[17]), "=f"(d[18]), "=f"(d[19]), "=f"(d[20]), "=f"(d[21]), "=f"(d[22]), "=f"(d[23]),
      "=f"(d[24]), "=f"(d[25]), "=f"(d[26]), "=f"(d[27]), "=f"(d[28]), "=f"(d[29]), "=f"(d[30]), "=f"(d[31])
    : "l"(da), "l"(db), "n"(TA), "n"(TB));
}

template <int TA, int TB>
__device__ __forceinline__ void wgmma_n96(float (&d)[48], uint64_t da, uint64_t db, int scale_d) {
  asm volatile("{\n.reg .pred p;\nsetp.ne.b32 p, %50, 0;\n"
    "wgmma.mma_async.sync.aligned.m64n96k16.f32.bf16.bf16 {"
    "%0, %1, %2, %3, %4, %5, %6, %7, %8, %9, %10, %11, %12, %13, %14, %15, "
    "%16, %17, %18, %19, %20, %21, %22, %23, %24, %25, %26, %27, %28, %29, %30, %31, "
    "%32, %33, %34, %35, %36, %37, %38, %39, %40, %41, %42, %43, %44, %45, %46, %47"
    "}, %48, %49, p, 1, 1, %51, %52;\n}\n"
    : "+f"(d[0]), "+f"(d[1]), "+f"(d[2]), "+f"(d[3]), "+f"(d[4]), "+f"(d[5]), "+f"(d[6]), "+f"(d[7]),
      "+f"(d[8]), "+f"(d[9]), "+f"(d[10]), "+f"(d[11]), "+f"(d[12]), "+f"(d[13]), "+f"(d[14]), "+f"(d[15]),
      "+f"(d[16]), "+f"(d[17]), "+f"(d[18]), "+f"(d[19]), "+f"(d[20]), "+f"(d[21]), "+f"(d[22]), "+f"(d[23]),
      "+f"(d[24]), "+f"(d[25]), "+f"(d[26]), "+f"(d[27]), "+f"(d[28]), "+f"(d[29]), "+f"(d[30]), "+f"(d[31]),
      "+f"(d[32]), "+f"(d[33]), "+f"(d[34]), "+f"(d[35]), "+f"(d[36]), "+f"(d[37]), "+f"(d[38]), "+f"(d[39]),
      "+f"(d[40]), "+f"(d[41]), "+f"(d[42]), "+f"(d[43]), "+f"(d[44]), "+f"(d[45]), "+f"(d[46]), "+f"(d[47])
    : "l"(da), "l"(db), "r"(scale_d), "n"(TA), "n"(TB));
}
template <int TA, int TB>
__device__ __forceinline__ void wgmma_n96_z(float (&d)[48], uint64_t da, uint64_t db) {
  asm volatile("{\n.reg .pred p;\nsetp.ne.b32 p, 0, 0;\n"
    "wgmma.mma_async.sync.aligned.m64n96k16.f32.bf16.bf16 {"
    "%0, %1, %2, %3, %4, %5, %6, %7, %8, %9, %10, %11, %12, %13, %14, %15, "
    "%16, %17, %18, %19, %20, %21, %22, %23, %24, %25, %26, %27, %28, %29, %30, %31, "
    "%32, %33, %34, %35, %36, %37, %38, %39, %40, %41, %42, %43, %44, %45, %46, %47"
    "}, %48, %49, p, 1, 1, %50, %51;\n}\n"
    : "=f"(d[0]), "=f"(d[1]), "=f"(d[2]), "=f"(d[3]), "=f"(d[4]), "=f"(d[5]), "=f"(d[6]), "=f"(d[7]),
      "=f"(d[8]), "=f"(d[9]), "=f"(d[10]), "=f"(d[11]), "=f"(d[12]), "=f"(d[13]), "=f"(d[14]), "=f"(d[15]),
      "=f"(d[16]), "=f"(d[17]), "=f"(d[18]), "=f"(d[19]), "=f"(d[20]), "=f"(d[21]), "=f"(d[22]), "=f"(d[23]),
      "=f"(d[24]), "=f"(d[25]), "=f"(d[26]), "=f"(d[27]), "=f"(d[28]), "=f"(d[29]), "=f"(d[30]), "=f"(d[31]),
      "=f"(d[32]), "=f"(d[33]), "=f"(d[34]), "=f"(d[35]), "=f"(d[36]), "=f"(d[37]), "=f"(d[38]), "=f"(d[39]),
      "=f"(d[40]), "=f"(d[41]), "=f"(d[42]), "=f"(d[43]), "=f"(d[44]), "=f"(d[45]), "=f"(d[46]), "=f"(d[47])
    : "l"(da), "l"(db), "n"(TA), "n"(TB));
}

template <int TA, int TB>
__device__ __forceinline__ void wgmma_n128(float (&d)[64], uint64_t da, uint64_t db, int scale_d) {
  asm volatile("{\n.reg .pred p;\nsetp.ne.b32 p, %66, 0;\n"
    "wgmma.mma_async.sync.aligned.m64n128k16.f32.bf16.bf16 {"
    "%0, %1, %2, %3, %4, %5, %6, %7, %8, %9, %10, %11, %12, %13, %14, %15, "
    "%16, %17, %18, %19, %20, %21, %22, %23, %24, %25, %26, %27, %28, %29, %30, %31, "
    "%32, %33, %34, %35, %36, %37, %38, %39, %40, %41, %42, %43, %44, %45, %46, %47, "
    "%48, %49, %50, %51, %52, %53, %54, %55, %56, %57, %58, %59, %60, %61, %62, %63"
    "}, %64, %65, p, 1, 1, %67, %68;\n}\n"
    : "+f"(d[0]), "+f"(d[1]), "+f"(d[2]), "+f"(d[3]), "+f"(d[4]), "+f"(d[5]), "+f"(d[6]), "+f"(d[7]),
      "+f"(d[8]), "+f"(d[9]), "+f"(d[10]), "+f"(d[11]), "+f"(d[12]), "+f"(d[13]), "+f"(d[14]), "+f"(d[15]),
      "+f"(d[16]), "+f"(d[17]), "+f"(d[18]), "+f"(d[19]), "+f"(d[20]), "+f"(d[21]), "+f"(d[22]), "+f"(d[23]),
      "+f"(d[24]), "+f"(d[25]), "+f"(d[26]), "+f"(d[27]), "+f"(d[28]), "+f"(d[29]), "+f"(d[30]), "+f"(d[31]),
      "+f"(d[32]), "+f"(d[33]), "+f"(d[34]), "+f"(d[35]), "+f"(d[36]), "+f"(d[37]), "+f"(d[38]), "+f"(d[39]),
      "+f"(d[40]), "+f"(d[41]), "+f"(d[42]), "+f"(d[43]), "+f"(d[44]), "+f"(d[45]), "+f"(d[46]), "+f"(d[47]),
      "+f"(d[48]), "+f"(d[49]), "+f"(d[50]), "+f"(d[51]), "+f"(d[52]), "+f"(d[53]), "+f"(d[54]), "+f"(d[55]),
      "+f"(d[56]), "+f"(d[57]), "+f"(d[58]), "+f"(d[59]), "+f"(d[60]), "+f"(d[61]), "+f"(d[62]), "+f"(d[63])
    : "l"(da), "l"(db), "r"(scale_d), "n"(TA), "n"(TB));
}
template <int TA, int TB>
__device__ __forceinline__ void wgmma_n128_z(float (&d)[64], uint64_t da, uint64_t db) {
  asm volatile("{\n.reg .pred p;\nsetp.ne.b32 p, 0, 0;\n"
    "wgmma.mma_async.sync.aligned.m64n128k16.f32.bf16.bf16 {"
    "%0, %1, %2, %3, %4, %5, %6, %7, %8, %9, %10, %11, %12, %13, %14, %15, "
    "%16, %17, %18, %19, %20, %21, %22, %23, %24, %25, %26, %27, %28, %29, %30, %31, "
    "%32, %33, %34, %35, %36, %37, %38, %39, %40, %41, %42, %43, %44, %45, %46, %47, "
    "%48, %49, %50, %51, %52, %53, %54, %55, %56, %57, %58, %59, %60, %61, %62, %63"
    "}, %64, %65, p, 1, 1, %66, %67;\n}\n"
    : "=f"(d[0]), "=f"(d[1]), "=f"(d[2]), "=f"(d[3]), "=f"(d[4]), "=f"(d[5]), "=f"(d[6]), "=f"(d[7]),
      "=f"(d[8]), "=f"(d[9]), "=f"(d[10]), "=f"(d[11]), "=f"(d[12]), "=f"(d[13]), "=f"(d[14]), "=f"(d[15]),
      "=f"(d[16]), "=f"(d[17]), "=f"(d[18]), "=f"(d[19]), "=f"(d[20]), "=f"(d[21]), "=f"(d[22]), "=f"(d[23]),
      "=f"(d[24]), "=f"(d[25]), "=f"(d[26]), "=f"(d[27]), "=f"(d[28]), "=f"(d[29]), "=f"(d[30]), "=f"(d[31]),
      "=f"(d[32]), "=f"(d[33]), "=f"(d[34]), "=f"(d[35]), "=f"(d[36]), "=f"(d[37]), "=f"(d[38]), "=f"(d[39]),
      "=f"(d[40]), "=f"(d[41]), "=f"(d[42]), "=f"(d[43]), "=f"(d[44]), "=f"(d[45]), "=f"(d[46]), "=f"(d[47]),
      "=f"(d[48]), "=f"(d[49]), "=f"(d[50]), "=f"(d[51]), "=f"(d[52]), "=f"(d[53]), "=f"(d[54]), "=f"(d[55]),
      "=f"(d[56]), "=f"(d[57]), "=f"(d[58]), "=f"(d[59]), "=f"(d[60]), "=f"(d[61]), "=f"(d[62]), "=f"(d[63])
    : "l"(da), "l"(db), "n"(TA), "n"(TB));
}

template <int TA, int TB>
__device__ __forceinline__ void wgmma_n160(float (&d)[80], uint64_t da, uint64_t db, int scale_d) {
  asm volatile("{\n.reg .pred p;\nsetp.ne.b32 p, %82, 0;\n"
    "wgmma.mma_async.sync.aligned.m64n160k16.f32.bf16.bf16 {"
    "%0, %1, %2, %3, %4, %5, %6, %7, %8, %9, %10, %11, %12, %13, %14, %15, "
    "%16, %17, %18, %19, %20, %21, %22, %23, %24, %25, %26, %27, %28, %29, %30, %31, "
    "%32, %33, %34, %35, %36, %37, %38, %39, %40, %41, %42, %43, %44, %45, %46, %47, "
    "%48, %49, %50, %51, %52, %53, %54, %55, %56, %57, %58, %59, %60, %61, %62, %63, "
    "%64, %65, %66, %67, %68, %69, %70, %71, %72, %73, %74, %75, %76, %77, %78, %79"
    "}, %80, %81, p, 1, 1, %83, %84;\n}\n"
    : "+f"(d[0]), "+f"(d[1]), "+f"(d[2]), "+f"(d[3]), "+f"(d[4]), "+f"(d[5]), "+f"(d[6]), "+f"(d[7]),
      "+f"(d[8]), "+f"(d[9]), "+f"(d[10]), "+f"(d[11]), "+f"(d[12]), "+f"(d[13]), "+f"(d[14]), "+f"(d[15]),
      "+f"(d[16]), "+f"(d[17]), "+f"(d[18]), "+f"(d[19]), "+f"(d[20]), "+f"(d[21]), "+f"(d[22]), "+f"(d[23]),
      "+f"(d[24]), "+f"(d[25]), "+f"(d[26]), "+f"(d[27]), "+f"(d[28]), "+f"(d[29]), "+f"(d[30]), "+f"(d[31]),
      "+f"(d[32]), "+f"(d[33]), "+f"(d[34]), "+f"(d[35]), "+f"(d[36]), "+f"(d[37]), "+f"(d[38]), "+f"(d[39]),
      "+f"(d[40]), "+f"(d[41]), "+f"(d[42]), "+f"(d[43]), "+f"(d[44]), "+f"(d[45]), "+f"(d[46]), "+f"(d[47]),
      "+f"(d[48]), "+f"(d[49]), "+f"(d[50]), "+f"(d[51]), "+f"(d[52]), "+f"(d[53]), "+f"(d[54]), "+f"(d[55]),
      "+f"(d[56]), "+f"(d[57]), "+f"(d[58]), "+f"(d[59]), "+f"(d[60]), "+f"(d[61]), "+f"(d[62]), "+f"(d[63]),
      "+f"(d[64]), "+f"(d[65]), "+f"(d[66]), "+f"(d[67]), "+f"(d[68]), "+f"(d[69]), "+f"(d[70]), "+f"(d[71]),
      "+f"(d[72]), "+f"(d[73]), "+f"(d[74]), "+f"(d[75]), "+f"(d[76]), "+f"(d[77]), "+f"(d[78]), "+f"(d[79])
    : "l"(da), "l"(db), "r"(scale_d), "n"(TA), "n"(TB));
}
template <int TA, int TB>
__device__ __forceinline__ void wgmma_n160_z(float (&d)[80], uint64_t da, uint64_t db) {
  asm volatile("{\n.reg .pred p;\nsetp.ne.b32 p, 0, 0;\n"
    "wgmma.mma_async.sync.aligned.m64n160k16.f32.bf16.bf16 {"
    "%0, %1, %2, %3, %4, %5, %6, %7, %8, %9, %10, %11, %12, %13, %14, %15, "
    "%16, %17, %18, %19, %20, %21, %22, %23, %24, %25, %26, %27, %28, %29, %30, %31, "
    "%32, %33, %34, %35, %36, %37, %38, %39, %40, %41, %42, %43, %44, %45, %46, %47, "
    "%48, %49, %50, %51, %52, %53, %54, %55, %56, %57, %58, %59, %60, %61, %62, %63, "
    "%64, %65, %66, %67, %68, %69, %70, %71, %72, %73, %74, %75, %76, %77, %78, %79"
    "}, %80, %81, p, 1, 1, %82, %83;\n}\n"
    : "=f"(d[0]), "=f"(d[1]), "=f"(d[2]), "=f"(d[3]), "=f"(d[4]), "=f"(d[5]), "=f"(d[6]), "=f"(d[7]),
      "=f"(d[8]), "=f"(d[9]), "=f"(d[10]), "=f"(d[11]), "=f"(d[12]), "=f"(d[13]), "=f"(d[14]), "=f"(d[15]),
      "=f"(d[16]), "=f"(d[17]), "=f"(d[18]), "=f"(d[19]), "=f"(d[20]), "=f"(d[21]), "=f"(d[22]), "=f"(d[23]),
      "=f"(d[24]), "=f"(d[25]), "=f"(d[26]), "=f"(d[27]), "=f"(d[28]), "=f"(d[29]), "=f"(d[30]), "=f"(d[31]),
      "=f"(d[32]), "=f"(d[33]), "=f"(d[34]), "=f"(d[35]), "=f"(d[36]), "=f"(d[37]), "=f"(d[38]), "=f"(d[39]),
      "=f"(d[40]), "=f"(d[41]), "=f"(d[42]), "=f"(d[43]), "=f"(d[44]), "=f"(d[45]), "=f"(d[46]), "=f"(d[47]),
      "=f"(d[48]), "=f"(d[49]), "=f"(d[50]), "=f"(d[51]), "=f"(d[52]), "=f"(d[53]), "=f"(d[54]), "=f"(d[55]),
      "=f"(d[56]), "=f"(d[57]), "=f"(d[58]), "=f"(d[59]), "=f"(d[60]), "=f"(d[61]), "=f"(d[62]), "=f"(d[63]),
      "=f"(d[64]), "=f"(d[65]), "=f"(d[66]), "=f"(d[67]), "=f"(d[68]), "=f"(d[69]), "=f"(d[70]), "=f"(d[71]),
      "=f"(d[72]), "=f"(d[73]), "=f"(d[74]), "=f"(d[75]), "=f"(d[76]), "=f"(d[77]), "=f"(d[78]), "=f"(d[79])
    : "l"(da), "l"(db), "n"(TA), "n"(TB));
}

__device__ __forceinline__ unsigned load_epoch(const Params& P, int role) {
  unsigned tag;
  asm volatile("ld.relaxed.gpu.global.u32 %0, [%1];" : "=r"(tag) : "l"(P.scr + G_EPOCH + 4 * role) : "memory");
  return tag;
}

__device__ __forceinline__ int unit_of(int ftype, int nt, int s, bool& ssm) {
  const int c = ftype * 4 + nt;
  ssm = false;
  if (s == 0) return c;
  if (s == 1) { ssm = true; return c; }
  if (s == 2) {
    if (!ftype) return 10 + nt;
    ssm = nt < 2;
    return ssm ? 8 + nt : 6 + nt;
  }
  if (s == 3) return 14 + c;
  return 23 + nt;
}

template <int MODE, bool ZERO>
__device__ __forceinline__ void unit_mma(float (&acc0)[64], float (&acc1)[64], float (&g0)[4], float (&g1)[4], uint32_t xa,
                                         uint32_t wa, uint32_t ga, int kk) {
  if (MODE == 1) {
    const uint64_t db = desc_k(xa + kk * 2);
    if (ZERO) { wgmma_n128_z<0, 0>(acc0, desc_k(wa), db); wgmma_n128_z<0, 0>(acc1, desc_k(wa + 512), db); }
    else { wgmma_n128<0, 0>(acc0, desc_k(wa + kk * 2), db, 1); wgmma_n128<0, 0>(acc1, desc_k(wa + 512 + kk * 2), db, 1); }
  } else {
    const uint64_t db = desc_mn(wa + kk * 128);
    if (ZERO) { wgmma_n128_z<0, 1>(acc0, desc_k(xa), db); wgmma_n128_z<0, 1>(acc1, desc_k(xa + 512), db); }
    else { wgmma_n128<0, 1>(acc0, desc_k(xa + kk * 2), db, 1); wgmma_n128<0, 1>(acc1, desc_k(xa + 512 + kk * 2), db, 1); }
    if (MODE == 2) {
      const uint64_t dg = ((uint64_t)1 << 32) | (uint64_t)(ga + kk * 2 + (1u << 16));
      if (ZERO) { wgmma_n8_z<0, 0>(g0, desc_k(xa), dg); wgmma_n8_z<0, 0>(g1, desc_k(xa + 512), dg); }
      else { wgmma_n8<0, 0>(g0, desc_k(xa + kk * 2), dg, 1); wgmma_n8<0, 0>(g1, desc_k(xa + 512 + kk * 2), dg, 1); }
    }
  }
}
template <int MODE>
__device__ __forceinline__ void unit_fence(float (&acc0)[64], float (&acc1)[64], float (&g0)[4], float (&g1)[4]) {
  fence_regs(acc0); fence_regs(acc1);
  if (MODE == 2) { fence_regs(g0); fence_regs(g1); }
}
template <int MODE, bool K0>
__device__ __forceinline__ uint32_t unit_kstep(float (&acc0)[64], float (&acc1)[64], float (&g0)[4], float (&g1)[4], uint32_t sb,
                                               int k, uint32_t& s, uint32_t& ph, bool first) {
  const uint32_t sb16 = (sb & 0x3FFFFu) >> 4;
  const uint32_t res = sb16 + (SM_RES >> 4) + k * (CH >> 4), ring = sb16 + (SM_RING >> 4) + s * (CH >> 4);
  const uint32_t xa = MODE == 2 ? ring : res, wa = MODE == 2 ? res : ring, ga = sb16 + (SM_GW >> 4) + k * 8;
  const uint32_t sp = (s + 3) & 3;
  s = (s + 1) & 3;
  ph ^= (s == 0);
  if (!K0) unit_fence<MODE>(acc0, acc1, g0, g1);
  wg_fence();
  unit_mma<MODE, K0>(acc0, acc1, g0, g1, xa, wa, ga, 0);
  unit_mma<MODE, false>(acc0, acc1, g0, g1, xa, wa, ga, 1);
  wg_commit();
  if (!K0) {
    wg_wait<1>();
    mbar_arrive_elect(sb + B_EMPTY1 + 8 * sp);
  }
  uint32_t ok = mbar_test(sb + B_FULL1 + 8 * s, ph);
  if (first) ok &= mbar_test(sb + B_XFULL + 8 * (k + 1), 0);
  unit_fence<MODE>(acc0, acc1, g0, g1);
  wg_fence();
  unit_mma<MODE, false>(acc0, acc1, g0, g1, xa, wa, ga, 2);
  unit_mma<MODE, false>(acc0, acc1, g0, g1, xa, wa, ga, 3);
  wg_commit();
  unit_fence<MODE>(acc0, acc1, g0, g1);
  return ok;
}
template <int MODE>
__device__ __forceinline__ float unit_mainloop(float (&acc0)[64], float (&acc1)[64], float (&g0)[4], float (&g1)[4], uint32_t sb,
                                              int it0, bool first, bool signal, int wg, int lane
) {
  uint32_t s = it0 & 3, ph = (it0 >> 2) & 1;
  if (first) mbar_wait(sb + B_XFULL, 0);
  mbar_wait(sb + B_FULL1 + 8 * s, ph);
  if ((threadIdx.x & 127) == 0) TR(it0, 2);
  if (it0 == 0) PROF_EV(55);
  uint32_t ok = unit_kstep<MODE, true>(acc0, acc1, g0, g1, sb, 0, s, ph, first);
#pragma unroll 1
  for (int k = 1; k < 10; k++) {
    if ((threadIdx.x & 127) == 0) TR(it0 + k, 1);
    if (!ok) {
      if (first) mbar_wait(sb + B_XFULL + 8 * k, 0);
      mbar_wait(sb + B_FULL1 + 8 * s, ph);
    }
    if ((threadIdx.x & 127) == 0) TR(it0 + k, 2);
    ok = unit_kstep<MODE, false>(acc0, acc1, g0, g1, sb, k, s, ph, first);
  }
  if (signal) bar_arrive(1 + (wg ^ 1), 256);
  wg_wait<0>();
  unit_fence<MODE>(acc0, acc1, g0, g1);
  return mbar_arrive_token(sb + B_EMPTY1 + 8 * ((s + 3) & 3));
}

__device__ __forceinline__ void block_end(uint32_t zero) {
  asm volatile("{\n.reg .pred p;\n.reg .u32 c;\nsetp.eq.u32 p, %0, 0;\n@p bra D;\n"
               "L:\nmov.u32 c, %%clock;\nsetp.lt.u32 p, c, %0;\n@p bra L;\nD:\n}" ::"r"(zero) : "memory");
}

__device__ __forceinline__ float chain(float x, float y, uint32_t zero) {
  return __uint_as_float(__float_as_uint(x) | (__float_as_uint(y) & zero));
}

template <bool PACED, int PIECE>
__device__ __forceinline__ void ffn_piece(const float (&a0)[64], const float (&a1)[64], unsigned char* tile, int w, int lane,
                                          float (&v)[NCH], uint32_t zero) {
  constexpr int mh = PIECE >> 2, hi = (PIECE >> 1) & 1, h = PIECE & 1;
  const int q = lane & 3, r = lane >> 2;
  const int m7 = 4 * (w & 1) + 2 * hi + (r & 1);
  const int m = (2 * mh + (w >> 1)) * 32 + (r >> 1) * 8 + m7;
  uint32_t p[4];
#pragma unroll
  for (int j = 0; j < 4; j++) {
    float o[2];
#pragma unroll
    for (int e = 0; e < 2; e++) {
      const int i = 4 * (4 * h + j) + 2 * hi + e, c = (8 * PIECE + 2 * j + e) % NCH;
      const float g = mh ? a1[i] : a0[i], u = mh ? a1[32 + i] : a0[32 + i];
      const float sg = fast_rcp(1.0f + fast_ex2(g * (PACED ? chain(-1.4426950408889634f, v[c], zero) : v[0])));
      o[e] = (g * sg) * u;
      if (PACED) v[c] = o[e];
    }
    p[j] = pack_bf16(o[0], o[1]);
  }
  st_v4(tile + m * 128 + (((4 * h + q) ^ m7) << 4), p[0], p[1], p[2], p[3]);
}
template <bool PACED, int N, int I = 0>
__device__ __forceinline__ void ffn_pieces(const float (&a0)[64], const float (&a1)[64], unsigned char* tile, int w, int lane,
                                           float (&v)[NCH], uint32_t zero) {
  if constexpr (I < N) {
    ffn_piece<PACED, I>(a0, a1, tile, w, lane, v, zero);
    ffn_pieces<PACED, N, I + 1>(a0, a1, tile, w, lane, v, zero);
  }
}

struct SsmCoef { cplx lam, c, l32, l64, mu; };
__device__ __forceinline__ float4 ssm_coef(const Params& P, int p) {
  const float lr = __bfloat162float(P.lre[p]), li = __bfloat162float(P.lim[p]);
  const float dt = __bfloat162float(__float2bfloat16_rn(expf(__bfloat162float(P.logdt[p]))));
  float sn, cs;
  sincospif(dt * li * 0.31830988618379067f, &sn, &cs);
  const float ex = expf(dt * lr);
  const float nr = ex * cs - 1.0f, ni = ex * sn, den = 1.0f / (lr * lr + li * li);
  return make_float4(ex * cs, ex * sn, (nr * lr + ni * li) * den, (ni * lr - nr * li) * den);
}
__device__ __forceinline__ SsmCoef ssm_powers(uint32_t addr) {
  SsmCoef o;
  asm volatile("ld.shared.v4.f32 {%0, %1, %2, %3}, [%4];" : "=f"(o.lam.r), "=f"(o.lam.i), "=f"(o.c.r), "=f"(o.c.i) : "r"(addr) : "memory");
  cplx t = o.lam;
#pragma unroll
  for (int i = 0; i < 5; i++) t = cmul(t, t);
  o.l32 = t;
  o.l64 = cmul(t, t);
  o.mu = cmul(o.l64, o.l64);
  return o;
}

__device__ __forceinline__ void agg_load(unsigned long long& a, unsigned long long& b, const void* p, int valid) {
  asm volatile("{\n.reg .pred p;\nsetp.ne.s32 p, %3, 0;\n@p ld.relaxed.gpu.global.v2.b64 {%0, %1}, [%2];\n}"
               : "+l"(a), "+l"(b) : "l"(p), "r"(valid) : "memory");
}

__device__ __forceinline__ void ssm_epilogue(const float (&vr)[64], const float (&vi)[64], const SsmCoef (&co)[2], unsigned char* scr, int rb,
                                             int cg, unsigned tag, int w, int lane, uint32_t zero, float prev
) {
  const int q = lane & 3, r = lane >> 2;
  char* agg = (char*)scr + G_AGG + ((cg * NRB + rb) * 64 + 16 * w + r) * 16;
  cplx s1[2];
#pragma unroll
  for (int hi = 0; hi < 2; hi++) {
    const cplx lam = P1DENSE && hi ? co[hi].lam : cplx{chain(co[hi].lam.r, prev, zero), chain(co[hi].lam.i, prev, zero)};
    cplx s = {vr[2 * hi], vi[2 * hi]};
#pragma unroll
    for (int t = 1; t < 32; t++) {
      const int i = 4 * (t >> 1) + 2 * hi + (t & 1);
      s = cfma(lam, s, cplx{vr[i], vi[i]});
    }
    s1[hi] = s;
    prev = s.r;
  }
#pragma unroll
  for (int hi = 0; hi < 2; hi++) {
    const cplx y = cshfl_up(s1[hi], 1);
    if (q >= 1) s1[hi] = cfma(co[hi].l32, y, s1[hi]);
  }
#pragma unroll
  for (int hi = 0; hi < 2; hi++) {
    const cplx y = cshfl_up(s1[hi], 2);
    if (q >= 2) s1[hi] = cfma(co[hi].l64, y, s1[hi]);
    const unsigned long long a = ((unsigned long long)tag << 32) | __float_as_uint(s1[hi].r);
    const unsigned long long b = ((unsigned long long)tag << 32) | __float_as_uint(s1[hi].i);
    asm volatile("{\n.reg .pred p;\nsetp.eq.s32 p, %3, 3;\n@p st.relaxed.gpu.global.v2.b64 [%0], {%1, %2};\n}"
                 ::"l"(agg + 128 * hi), "l"(a), "l"(b), "r"(q) : "memory");
  }
  PROF_EV(20 + slot * 2);
  cplx h0[2], mq[2], m4[2], lq[2];
#pragma unroll
  for (int hi = 0; hi < 2; hi++) {
    const cplx y = cshfl_up(s1[hi], 1), one = {1.f, 0.f};
    h0[hi] = q >= 1 ? cmul(co[hi].c, y) : cplx{0.f, 0.f};
    prev = y.i;
    const cplx mu2 = cmul(co[hi].mu, co[hi].mu);
    m4[hi] = cmul(mu2, mu2);
    mq[hi] = cmul((q & 1) ? co[hi].mu : one, (q & 2) ? mu2 : one);
    lq[hi] = cmul(cmul((q & 1) ? co[hi].l32 : one, (q & 2) ? co[hi].l64 : one), co[hi].c);
  }
  const int nv = rb - q;
  const char* src = agg - (1 + q) * 1024;
  unsigned long long ea[2][4], eb[2][4];
  float wr[64], wn[64];
#pragma unroll
  for (int t = 0; t < 64; t++) {
    if (t == GATHER_AT) {
      const char* sp = src + (__float_as_uint(prev) & zero);
#pragma unroll
      for (int m = 0; m < 4; m++)
#pragma unroll
        for (int h2 = 0; h2 < 2; h2++) {
          asm volatile("{\n.reg .pred p;\nsetp.ne.s32 p, %3, 0;\n@p ld.relaxed.gpu.global.v2.b64 {%0, %1}, [%2];\n}"
                       : "=l"(ea[h2][m]), "=l"(eb[h2][m]) : "l"(sp + 128 * h2 - 4096 * m), "r"((int)(4 * m < nv)) : "memory");
        }
    }
    const int hi = t >> 5, i = 4 * ((t & 31) >> 1) + 2 * hi + (t & 1);
    const float cr = t % PMCH == 0 ? chain(co[hi].c.r, prev, zero) : prev, ci = co[hi].c.i, a = vr[i], b = vi[i];
    wr[i] = fmaf(-ci, b, cr * a);
    wn[i] = fmaf(-ci, a, -cr * b);
    prev = (t + 1) % PMCH == 0 ? wr[i] : cr;
  }
  int spin = 0;
  while (true) {
    bool ok = true;
#pragma unroll
    for (int m = 0; m < 4; m++) {
      const unsigned x = ((unsigned)(ea[0][m] >> 32) ^ tag) | ((unsigned)(eb[0][m] >> 32) ^ tag) |
                         ((unsigned)(ea[1][m] >> 32) ^ tag) | ((unsigned)(eb[1][m] >> 32) ^ tag);
      ok = ok && (x == 0 || 4 * m >= nv);
    }
    if (__all_sync(0xffffffffu, ok)) break;
#pragma unroll
    for (int m = 0; m < 4; m++)
#pragma unroll
      for (int hi = 0; hi < 2; hi++) agg_load(ea[hi][m], eb[hi][m], src + 128 * hi - 4096 * m, 4 * m < nv);
    trap_if_over(++spin, 1 << 21);
  }
  PROF_EV(21 + slot * 2);
#pragma unroll
  for (int hi = 0; hi < 2; hi++) {
    cplx a = {0.f, 0.f};
#pragma unroll
    for (int m = 3; m >= 0; m--)
      if (4 * m < nv) a = cfma(m4[hi], a, cplx{__uint_as_float((unsigned)ea[hi][m]), __uint_as_float((unsigned)eb[hi][m])});
    a = cmul(a, mq[hi]);
    a.r += __shfl_xor_sync(0xffffffffu, a.r, 1); a.i += __shfl_xor_sync(0xffffffffu, a.i, 1);
    a.r += __shfl_xor_sync(0xffffffffu, a.r, 2); a.i += __shfl_xor_sync(0xffffffffu, a.i, 2);
    h0[hi] = cfma(lq[hi], a, h0[hi]);
  }
  unsigned char* tile = scr + G_H + (size_t)((rb * NCG + cg) * 2) * CH + (16 * w + r) * 128;
  unsigned char* t0 = tile + ((q ^ r) << 4);
  unsigned char* t1 = tile + (((4 + q) ^ r) << 4);
  prev = h0[1].i;
#pragma unroll
  for (int hi = 0; hi < 2; hi++) {
    const cplx lam = co[hi].lam;
    float hr = P2DENSE ? h0[hi].r : chain(h0[hi].r, prev, zero), hn = P2DENSE ? -h0[hi].i : chain(-h0[hi].i, prev, zero);
#pragma unroll
    for (int i8 = 0; i8 < 4; i8++) {
      uint32_t pr[4], pi[4];
#pragma unroll
      for (int jj = 0; jj < 4; jj++) {
        float fr[2], fn[2];
#pragma unroll
        for (int e = 0; e < 2; e++) {
          const int i = 4 * (4 * i8 + jj) + 2 * hi + e;
          const float nr = fmaf(lam.r, hr, fmaf(lam.i, hn, wr[i]));
          const float nn = fmaf(lam.r, hn, fmaf(-lam.i, hr, wn[i]));
          fr[e] = hr = nr; fn[e] = hn = nn;
        }
        pr[jj] = pack_bf16(fr[0], fr[1]);
        pi[jj] = pack_bf16(fn[0], fn[1]);
      }
      unsigned char* a = ((i8 & 1) ? t1 : t0) + (i8 >> 1) * 8192 + hi * 1024;
      st_v4(a, pr[0], pr[1], pr[2], pr[3]);
      st_v4(a + CH, pi[0], pi[1], pi[2], pi[3]);
      if (SF) block_end(zero);
    }
    prev = hr;
  }
}

__device__ __forceinline__ void ldmatrix4(uint32_t* r, uint32_t addr) {
  asm volatile("ldmatrix.sync.aligned.m8n8.x4.shared.b16 {%0, %1, %2, %3}, [%4];"
               : "=r"(r[0]), "=r"(r[1]), "=r"(r[2]), "=r"(r[3]) : "r"(addr) : "memory");
}

template <bool F, bool K0, int NA>
__device__ __forceinline__ void p2_mma(float (&acc)[NA], float (&acb)[32], uint32_t a, uint32_t b, uint32_t lbo96) {
  if (!K0) { fence_regs(acc); if (F) fence_regs(acb); }
  wg_fence();
#pragma unroll
  for (int kk = 0; kk < 4; kk++) {
    if constexpr (F) {
      const uint64_t d96 = ((uint64_t)0x40000040u << 32) | (uint64_t)(b + kk * 128 + lbo96);
      if (K0 && kk == 0) { wgmma_n96_z<0, 1>(acc, desc_k(a), d96); wgmma_n64_z<0, 1>(acb, desc_k(a), desc_mn(b + 512)); }
      else { wgmma_n96<0, 1>(acc, desc_k(a + kk * 2), d96, 1); wgmma_n64<0, 1>(acb, desc_k(a + kk * 2), desc_mn(b + 512 + kk * 128), 1); }
    } else {
      if (K0 && kk == 0) wgmma_n160_z<1, 0>(acc, desc_mn(a), desc_k(b));
      else wgmma_n160<1, 0>(acc, desc_mn(a + kk * 128), desc_k(b + kk * 2), 1);
    }
  }
  wg_commit();
  fence_regs(acc);
  if (F) fence_regs(acb);
}

template <bool F>
__device__ __forceinline__ void phase2(const Params& P, uint32_t sb, int rb, int nt, int wg, int w, int lane,
                                       const float (&u0)[64], const float (&u1)[64], unsigned char* tile
) {
  constexpr int NK = F ? NFC : 2 * NCG;
  const int q = lane & 3, r = lane >> 2, warp = wg * 4 + w;
  if (elect_one()) mbar_expect_tx(sb + B_RECV + 8 * warp, 2560);
  asm volatile("barrier.cluster.wait.acquire.aligned;" ::: "memory");
  const uint32_t peer = F ? 0 : 1;
  const uint32_t sb16 = (sb & 0x3FFFFu) >> 4;
  float acc[F ? 48 : 80], acb[32];
  const int rot = (F && (nt & 1)) ? 1 : 0;
  const uint32_t lbo96 = (1024u + 4u * rot) << 16;
#define ACC(i) (F && (i) >= 48 ? acb[(i) >= 48 ? (i) - 48 : 0] : acc[F && (i) >= 48 ? 0 : (i)])
  PROF_EV(32 + wg * 8 + 0);
  mbar_wait(sb + B_FULL2, 0);
  p2_mma<F, true>(acc, acb, sb16 + wg * 512, sb16 + (CH >> 4), lbo96);
  int s = 1, ph = 0;
  float v[NCH] = {};
#define P2_STEP_WITH_PIECE(K)                                                                                    \
  if constexpr (NPRE + (K) < 8) {                                                                                \
    if (wg == 1) ffn_piece<true, (NPRE + (K)) & 7>(u0, u1, tile, w, lane, v, P.zero);                            \
    if (NPRE + (K) == 7 && wg == 1) bar_arrive(4, 160);                                                          \
    mbar_wait(sb + B_FULL2 + 8 * (((K) + 1) % 5), (((K) + 1) / 5) & 1);                                          \
    p2_mma<F, false>(acc, acb, sb16 + (((K) + 1) % 5) * (ST2 >> 4) + wg * 512,                                   \
                     sb16 + (((K) + 1) % 5) * (ST2 >> 4) + (CH >> 4), lbo96);                                    \
    wg_wait<1>();                                                                                                \
    mbar_arrive_elect(sb + B_EMPTY2 + 8 * ((K) % 5));                                                            \
  }
  P2_STEP_WITH_PIECE(0) P2_STEP_WITH_PIECE(1) P2_STEP_WITH_PIECE(2) P2_STEP_WITH_PIECE(3)
  P2_STEP_WITH_PIECE(4) P2_STEP_WITH_PIECE(5) P2_STEP_WITH_PIECE(6) P2_STEP_WITH_PIECE(7)
#undef P2_STEP_WITH_PIECE
  if (NPRE == 8 && wg == 1) bar_arrive(4, 160);
  s = (9 - NPRE) % 5;
  ph = ((9 - NPRE) / 5) & 1;
#pragma unroll 1
  for (int k = 9 - NPRE; k < NK; k++) {
    if (k == NK - 4 && wg == 1) {
      wg_wait<0>();
      if (elect_one()) mbar_arrive_remote(mapa(sb + B_PEER, peer));
      if (STAG) bar_sync(6, 256);
    }
    if (threadIdx.x == 128) TR(50 + k, 1);
    { PROF_T0; mbar_wait(sb + B_FULL2 + 8 * s, ph); PROF_ACC(pw); }
    if (threadIdx.x == 128) TR(50 + k, 2);
    p2_mma<F, false>(acc, acb, sb16 + s * (ST2 >> 4) + wg * 512, sb16 + s * (ST2 >> 4) + (CH >> 4), lbo96);
    wg_wait<1>();
    if (k < NK - 4) mbar_arrive_elect(sb + B_EMPTY2 + 8 * (s == 0 ? 4 : s - 1));
    else if (k == NK - 4 && wg == 0 && elect_one()) mbar_arrive_remote(mapa(sb + B_PEER, peer));
    if (++s == 5) { s = 0; ph ^= 1; }
  }
  if (STAG && wg == 0) bar_arrive(6, 256);
  const int lrow = 8 * (2 * wg + (w >> 1));
  const int tk = 64 * (w & 1) + (F ? 32 : 0) + lrow + r;
#define CB(n) (!F ? (n) : (n) < 2 ? (n) + rot : (n) == 2 ? 4 - 4 * rot : (n) - 1 + rot)
  constexpr int RSLOT = NK % 5, RSLOT_PEER = F ? (2 * NCG) % 5 : NFC % 5;
  const uint32_t rdst = mapa(sb + RSLOT_PEER * ST2 + warp * 2560 + lane * 16, peer);
  const uint32_t rbar = mapa(sb + B_RECV + 8 * warp, peer);
  const bool odd = q & 1;
  const uint32_t rsrc = sb + RSLOT * ST2 + warp * 2560 + (lane & ~1) * 16 + (odd ? 8 : 0);
  float* orow = P.out + (size_t)(rb * 128 + tk) * DM + 160 * nt + (odd ? 2 * q + 6 : 2 * q);
  constexpr int OS = F ? 0 : 2, OK = F ? 2 : 0;
  mbar_wait_cluster(sb + B_PEER, 0);
  wg_wait<0>();
  fence_regs(acc);
  if (F) fence_regs(acb);
  PROF_EV(32 + wg * 8 + 1);
#pragma unroll
  for (int n = 0; n < 5; n++) {
    uint32_t p[4];
#pragma unroll
    for (int i = 0; i < 4; i++) p[i] = pack_bf16(ACC(16 * n + 4 * i + OS), ACC(16 * n + 4 * i + OS + 1));
    asm volatile("st.async.weak.shared::cluster.mbarrier::complete_tx::bytes.v4.b32 [%0], {%1, %2, %3, %4}, [%5];"
                 ::"r"(rdst + CB(n) * 512), "r"(p[0]), "r"(p[2]), "r"(p[1]), "r"(p[3]), "r"(rbar) : "memory");
  }
  float g;
  uint32_t xd[20];
  mbar_wait(sb + B_G, 0);
  asm volatile("ld.shared.f32 %0, [%1];" : "=f"(g) : "r"(sb + SM_G + 4 * tk) : "memory");
  mbar_wait(sb + B_XS, 0);
  {
    const uint32_t xa = sb + SM_XS + (w & 1) * 10752 + (lrow + (lane & 7)) * 336 + (lane >> 3) * 16;
    const uint32_t da = sb + SM_XS + 21504 + (lane >> 3) * 16;
#pragma unroll
    for (int n = 0; n < 5; n++) {
      uint32_t xv[4], dv[4];
      ldmatrix4(xv, xa + CB(n) * 64);
      ldmatrix4(dv, da + CB(n) * 64);
#pragma unroll
      for (int i = 0; i < 4; i++) asm("mul.bf16x2 %0, %1, %2;" : "=r"(xd[4 * n + i]) : "r"(xv[i]), "r"(dv[i]));
    }
  }
  const float sk = F ? 1.0f - g : 2.0f * g, sr = F ? 2.0f * g : 1.0f - g;
  float o[40];
#pragma unroll
  for (int i = 0; i < 10; i++) {
    float a[2], b[2];
#pragma unroll
    for (int e = 0; e < 2; e++) {
      const float u0 = fmaf(ACC(8 * i + OK + e), sk, g * (e ? bf_hi(xd[2 * i]) : bf_lo(xd[2 * i])));
      const float u1 = fmaf(ACC(8 * i + 4 + OK + e), sk, g * (e ? bf_hi(xd[2 * i + 1]) : bf_lo(xd[2 * i + 1])));
      a[e] = odd ? u1 : u0;
      b[e] = __shfl_xor_sync(0xffffffffu, odd ? u0 : u1, 1);
    }
    o[4 * i] = odd ? b[0] : a[0]; o[4 * i + 1] = odd ? b[1] : a[1];
    o[4 * i + 2] = odd ? a[0] : b[0]; o[4 * i + 3] = odd ? a[1] : b[1];
  }
  fence_regs(o);
  mbar_wait_cluster(sb + B_RECV + 8 * warp, 0);
  PROF_EV(32 + wg * 8 + 2);
#pragma unroll
  for (int n = 0; n < 5; n++) {
    uint32_t lo[2], hi[2];
    asm volatile("ld.shared.v2.b32 {%0, %1}, [%2];" : "=r"(lo[0]), "=r"(lo[1]) : "r"(rsrc + CB(n) * 512) : "memory");
    asm volatile("ld.shared.v2.b32 {%0, %1}, [%2];" : "=r"(hi[0]), "=r"(hi[1]) : "r"(rsrc + CB(n) * 512 + 16) : "memory");
#pragma unroll
    for (int h = 0; h < 2; h++) {
      const int i = 2 * n + h;
      *(float4*)(orow + 32 * CB(n) + 16 * h) = make_float4(fmaf(bf_lo(lo[h]), sr, o[4 * i]), fmaf(bf_hi(lo[h]), sr, o[4 * i + 1]),
                                                           fmaf(bf_lo(hi[h]), sr, o[4 * i + 2]), fmaf(bf_hi(hi[h]), sr, o[4 * i + 3]));
    }
  }
  PROF_EV(32 + wg * 8 + 3);
#undef ACC
#undef CB
}

template <bool USE_SMID>
__global__ void __launch_bounds__(384, 1) __cluster_dims__(2, 1, 1) fused_kernel(const __grid_constant__ Params P) {
  extern __shared__ __align__(1024) unsigned char smem_raw[];
  const uint32_t sb = smem_u32(smem_raw);
  trap_if_over((int)(sb & 1023u), 0);
  const int warp = __shfl_sync(0xffffffffu, threadIdx.x >> 5, 0), lane = threadIdx.x & 31;
  if (warp == 10 && elect_one()) { prefetch_map(&P.x); prefetch_map(&P.wg); prefetch_map(&P.wu); }
  uint32_t ftype, smid;
  asm("mov.u32 %0, %%cluster_ctarank;" : "=r"(ftype));
  asm("mov.u32 %0, %%smid;" : "=r"(smid));
  const int tp = USE_SMID ? (int)(smid >> 1) : (int)(blockIdx.x >> 1);
  int gpc, idx;
  bool extra = false;
  if (tp < 32) { gpc = tp & 7; idx = tp >> 3; }
  else if (tp < 60) { gpc = 1 + (tp - 32) % 7; idx = 4 + (tp - 32) / 7; }
  else if (tp < 62) { gpc = 0; idx = tp - 60; extra = true; }
  else { gpc = 0; idx = tp - 58; }
  const int rb = extra ? (idx * 2 + ftype) * 4 : MAP == 0 ? 2 * gpc + (idx >> 2) : MAP == 1 ? 4 * (gpc >> 1) + (idx & 3) : 8 * (gpc >> 2) + idx;
  const int nt = MAP == 0 ? idx & 3 : MAP == 1 ? 2 * (gpc & 1) + (idx >> 2) : gpc & 3;
  const int role = tp * 2 + ftype;
  const int nslots = (extra || ftype) ? 4 : 5;

  if (warp == 8) PROF_EV(58);
  const int fc0 = extra ? EXTRA_FC : ftype * 4 + nt;
  if (warp < 8 && EPF) {
    const int t = threadIdx.x;
    const char* a = t < 128 ? P.p_x + (size_t)(rb * 128 + t) * (DM * 2) : (t < 192 ? P.p_wg : P.p_wu) + (size_t)(t & 63) * (FF * 2) + fc0 * 128;
    asm volatile("prefetch.global.L2 [%0];" ::"l"(a));
    if (EPF > 1) asm volatile("prefetch.global.L2 [%0];" ::"l"(a + (t < 128 ? 128 : 64 * FF * 2)));
  }
  if (warp == 8) {
#pragma unroll 1
    for (int k = 0; k < 4; k++) {
      const uint32_t res = sb + SM_RES + k * CH, ring = sb + SM_RING + k * CH;
      const uint32_t bx = sb + B_XFULL + 8 * k, bf = sb + B_FULL1 + 8 * k;
      if (elect_one()) {
        if (k == 0) {
          mbar_init(bx, 1);
          mbar_init(bf, 1);
          asm volatile("fence.mbarrier_init.release.cluster;" ::: "memory");
        }
        mbar_expect_tx(bx, extra && k == 0 ? CH + 1280 : CH);
        mbar_expect_tx(bf, CH);
        tma5d(extra ? ring : res, &P.x, 64 * k, rb, extra ? bf : bx);
        tma2d(extra ? res : ring, &P.wg, 64 * fc0, 64 * k, extra ? bx : bf);
        tma2d((extra ? res : ring) + 8192, &P.wu, 64 * fc0, 64 * k, extra ? bx : bf);
        if (k == 0) {
          if (extra) bulk_load(sb + SM_GW, P.gatew, 1280, bx);
#pragma unroll
          for (int i = 1; i < 18; i++)
            if (i != 10) mbar_init(sb + SM_BAR + 8 * i, i < 14 ? 1 : 4);
          asm volatile("fence.mbarrier_init.release.cluster;" ::: "memory");
        }
      }
      if (k == 0) {
        __syncwarp();
        bar_arrive(0, 384);
        PROF_EV(57);
      }
    }
  } else {
    if (warp == 9 && elect_one()) {
#pragma unroll
      for (int i = 18; i < 40; i++) mbar_init(sb + SM_BAR + 8 * i, i < 23 ? 1 : i < 28 ? 8 : i == 28 ? 32 : i == 29 ? 8 : i == 39 ? 128 : 1);
      asm volatile("st.shared.u32 [%0], %1;" ::"r"(sb + SM_READY), "r"(0) : "memory");
      asm volatile("fence.mbarrier_init.release.cluster;" ::: "memory");
    }
    __syncwarp();
    bar_sync(0, 384);
  }
  asm volatile("barrier.cluster.arrive.relaxed.aligned;" ::: "memory");

  if (warp >= 8) {
    asm volatile("setmaxnreg.dec.sync.aligned.u32 40;");
    if (warp == 8) {
      int it = 4;
#pragma unroll 1
      for (int slot = 0; slot < nslots; slot++) {
        bool ssm = false;
        const int id = extra ? 0 : unit_of(ftype, nt, slot, ssm);
        const CUtensorMap* m0 = ssm ? &P.bre : &P.wg;
        const int c0 = ssm ? 0 : 64 * id, c1 = ssm ? 64 * id : 0, d0 = ssm ? 64 : 0;
#pragma unroll 1
        for (int k = slot == 0 ? 4 : 0; k < 10; k++, it++) {
          const int s = it & 3;
          const uint32_t ring = sb + SM_RING + s * CH, bf = sb + B_FULL1 + 8 * s;
          if (slot == 0 && elect_one()) {
            const uint32_t res = sb + SM_RES + k * CH, bx = sb + B_XFULL + 8 * k;
            mbar_expect_tx(bx, CH);
            if (!extra) tma5d(res, &P.x, 64 * k, rb, bx);
            else { tma2d(res, &P.wg, 64 * EXTRA_FC, 64 * k, bx); tma2d(res + 8192, &P.wu, 64 * EXTRA_FC, 64 * k, bx); }
          }
          { PROF_T0; mbar_wait(sb + B_EMPTY1 + 8 * s, ((it >> 2) & 1) ^ 1); PROF_ACC(pw1); }
          TR(it, 0);
          if (elect_one()) {
            mbar_expect_tx(bf, CH);
            if (extra) tma5d(ring, &P.x, 64 * k, rb + slot, bf);
            else {
              tma2d(ring, m0, c0 + d0 * k, c1 + (64 - d0) * k, bf);
              tma2d(ring + 8192, m0 + 1, c0 + d0 * k, c1 + (64 - d0) * k, bf);
            }
          }
        }
      }
      if (!extra) {
        const int nk = ftype ? NFC : 2 * NCG;
        const int dc = 160 * nt + ((nt & 1) ? 32 : 0);
        const unsigned char* asrc = P.scr + (ftype ? G_ACT + (size_t)(rb * NFC) * CH : G_H + (size_t)(rb * 2 * NCG) * CH);
        int s = 0, ph = 1;
        uint32_t ready = 0;
#pragma unroll 1
        for (int k2 = 0; k2 < nk; k2++) {
          if (k2 >= 5) {
            PROF_T0; mbar_wait(sb + B_EMPTY2 + 8 * s, ph); PROF_ACC(pw2);
          } else if (k2 == 2 || k2 == 3) {
            mbar_wait(sb + B_EMPTY1 + 8 * (it & 3), ((it >> 2) & 1) ^ 1);
            it++;
            mbar_wait(sb + B_EMPTY1 + 8 * (it & 3), ((it >> 2) & 1) ^ 1);
            it++;
          }
          TR(50 + k2, 0);
          const uint32_t st = sb + s * ST2, bf = sb + B_FULL2 + 8 * s;
          if (elect_one()) {
            if (ftype) {
              mbar_expect_tx(bf, 40960);
              tma5d(st + CH, &P.wd, dc, 2 * k2, bf);
              tma5d(st + CH + 8192, &P.wd, dc + 64, 2 * k2, bf);
              tma5d(st + CH + 16384, &P.wd, 128 + 320 * (nt >> 1), 2 * k2, bf);
            } else {
              mbar_expect_tx(bf, 36864);
              tma2d(st + CH, &P.cre + (k2 & 1), 64 * (k2 >> 1), 160 * nt, bf);
            }
          }
          const uint32_t need = ftype ? k2 : k2 >> 1;
          if (ready <= need) {
            int spin = 0;
            PROF_T0;
            do {
              asm volatile("ld.acquire.cta.shared.u32 %0, [%1];" : "=r"(ready) : "r"(sb + SM_READY) : "memory");
              trap_if_over(++spin, 1 << 26);
            } while (ready <= need);
            asm volatile("fence.proxy.async.global;" ::: "memory");
            PROF_ACC(pw3);
          }
          if (elect_one()) {
            bulk_load(st, asrc + (size_t)k2 * CH, CH, bf);
            if (k2 == XSK) {
              mbar_expect_tx(sb + B_XS, 21824);
              tma2d(sb + SM_XS, &P.xs, 160 * nt, rb * 128 + 32 * ftype, sb + B_XS);
              tma2d(sb + SM_XS + 10752, &P.xs, 160 * nt, rb * 128 + 64 + 32 * ftype, sb + B_XS);
              bulk_load(sb + SM_XS + 21504, P.dskip + 160 * nt, 320, sb + B_XS);
            }
          }
          if (++s == 5) { s = 0; ph ^= 1; }
        }
      }
    } else if (warp == 9) {
      const unsigned want = load_epoch(P, role) + 1;
      if (elect_one()) {
        prefetch_map(&P.bre); prefetch_map(&P.bim);
        if (ftype) prefetch_map(&P.wd); else { prefetch_map(&P.cre); prefetch_map(&P.cim); }
        prefetch_map(&P.xs);
      }
      for (int slot = 0; slot < nslots; slot++) {
        bool ssm = false;
        const int id = extra ? EXTRA_FC : unit_of(ftype, nt, slot, ssm);
        bar_sync(3 + ((slot + nslots) & 1), 160);
        if (elect_one()) {
          asm volatile("fence.acq_rel.gpu;" ::: "memory");
          asm volatile("st.relaxed.gpu.global.u32 [%0], %1;" ::"l"(P.scr + (ssm ? G_FLAG_H : G_FLAG_ACT) + 4 * ((extra ? rb + slot : rb) * 32 + id)), "r"(want) : "memory");
        }
        __syncwarp();
      }
      if (extra && lane == 0) asm volatile("red.relaxed.gpu.global.add.u32 [%0], 1;" ::"l"(P.scr + G_EPOCH + 4 * role) : "memory");
    } else if (warp == 10 && !extra) {
      const unsigned want = load_epoch(P, role) + 1;
      const int nf = ftype ? NFC : NCG;
      const unsigned char* fl = P.scr + (lane == 31 ? G_FLAG_ACT + 4 * EXTRA_FC : (ftype ? G_FLAG_ACT : G_FLAG_H) + 4 * lane) + 128 * rb;
      mbar_wait(sb + B_XFULL + 8 * 9, 0);
      __nanosleep(4000);
      uint32_t last = 0;
      int spin = 0;
      while (last < 32) {
        unsigned v = want;
        if (lane < nf || lane == 31) asm volatile("ld.acquire.gpu.global.u32 %0, [%1];" : "=r"(v) : "l"(fl) : "memory");
        const unsigned miss = __ballot_sync(0xffffffffu, v != want);
        const uint32_t n = miss ? __ffs(miss) - 1 : 32;
        __syncwarp();
        if (n > last) {
          last = n;
          if (lane == 0) asm volatile("st.release.cta.shared.u32 [%0], %1;" ::"r"(sb + SM_READY), "r"(n) : "memory");
        } else {
          __nanosleep(200);
        }
        trap_if_over(++spin, 1 << 22);
      }
      float4 gv;
      asm volatile("ld.relaxed.gpu.global.v4.f32 {%0, %1, %2, %3}, [%4];" : "=f"(gv.x), "=f"(gv.y), "=f"(gv.z), "=f"(gv.w) : "l"(P.scr + G_GATE + rb * 512 + 16 * lane) : "memory");
      asm volatile("st.shared.v4.f32 [%0], {%1, %2, %3, %4};" ::"r"(sb + SM_G + 16 * lane), "f"(gv.x), "f"(gv.y), "f"(gv.z), "f"(gv.w) : "memory");
      mbar_arrive(sb + B_G);
      if (lane == 0) asm volatile("red.relaxed.gpu.global.add.u32 [%0], 1;" ::"l"(P.scr + G_EPOCH + 4 * role) : "memory");
    } else if (warp == 11 && !extra) {
      const int pc = (rb * 4 + nt) * 2 + ftype;
      const char* wrow = (lane & 1 ? P.p_wu : P.p_wg) + (size_t)(pc * 5 + (lane >> 1)) * (FF * 2);
      mbar_wait(sb + B_XFULL + 8 * PF0, 0);
      if (lane < 2) l2_prefetch((lane ? P.p_bim : P.p_bre) + pc * 5120, 5120);
      mbar_wait(sb + B_XFULL + 8 * 9, 0);
      if (lane < 10) l2_prefetch(wrow + 8 * 128, 6 * 128);
      if (lane < 2) l2_prefetch((lane ? P.p_bim : P.p_bre) + 655360 + pc * 1280, 1280);
      __nanosleep(PFD);
      if (lane < 10) l2_prefetch(wrow + 14 * 128, 8 * 128);
      __nanosleep(PFD / 2);
      if (lane == 0) l2_prefetch(P.p_wd + pc * 8640, 8640);
      __nanosleep(PFD / 2);
      if (lane < 10) l2_prefetch(wrow + 23 * 128, 4 * 128);
      if (lane == 0) l2_prefetch(P.p_wd + 1105920 + pc * 8640, 8640);
      __nanosleep(PFD / 2);
      if (lane < 2) l2_prefetch((lane ? P.p_cim : P.p_cre) + pc * 6400, 6400);
    }
    __syncwarp();
    asm volatile("barrier.cluster.wait.acquire.aligned;" ::: "memory");
  } else {
    const int wg = warp >> 2, w = warp & 3;
    if (((wg + nslots) & 1) != 0) mbar_wait(sb + B_XFULL, 0);
    asm volatile("setmaxnreg.inc.sync.aligned.u32 232;");
    if (extra) {
#pragma unroll 1
      for (int slot = wg; slot < 4; slot += 2) {
        float acc0[64], acc1[64], g0[4], g1[4];
        if (slot > 0) bar_sync(1 + wg, 256);
        PROF_EV(slot * 4 + 0);
        const float tok = unit_mainloop<2>(acc0, acc1, g0, g1, sb, slot * 10, slot < 2, slot < 3, wg, lane PROF_ARGS);
        PROF_EV(slot * 4 + 1);
        if ((lane & 3) == 0) {
#pragma unroll
          for (int i = 0; i < 4; i++) {
            const int c = 64 * (i >> 1) + 16 * w + 8 * (i & 1) + (lane >> 2);
            const float z = (i >> 1) ? g1[2 * (i & 1)] : g0[2 * (i & 1)];
            ((float*)(P.scr + G_GATE))[(rb + slot) * 128 + 32 * ((c >> 1) & 3) + 2 * (c >> 3) + (c & 1)] = 1.0f / (1.0f + expf(-z));
          }
        }
        unsigned char* tile = P.scr + G_ACT + (size_t)((rb + slot) * NFC + EXTRA_FC) * CH;
        float v[NCH];
#pragma unroll
        for (int i = 0; i < NCH; i++) v[i] = tok;
        ffn_pieces<true, 8>(acc0, acc1, tile, w, lane, v, P.zero);
        PROF_EV(slot * 4 + 2);
        bar_arrive(3 + wg, 160);
      }
      asm volatile("barrier.cluster.wait.acquire.aligned;" ::: "memory");
    } else {
#pragma unroll 1
      for (int slot = (wg + nslots) & 1; slot < nslots - 1; slot += 2) {
        bool ssm = false;
        const int id = unit_of(ftype, nt, slot, ssm);
        const bool signal = true;
        float acc0[64], acc1[64], g0[4], g1[4];
        if (ssm) {
          const unsigned tag = load_epoch(P, role);
          if (slot == 1) {
            const int t = threadIdx.x & 127;
            const float4 cf = ssm_coef(P, t < 64 ? 64 * id + t : 512 + 64 * (nt & 1) + t - 64);
            asm volatile("st.shared.v4.f32 [%0], {%1, %2, %3, %4};" ::"r"(sb + SM_GW + 16 * t), "f"(cf.x), "f"(cf.y), "f"(cf.z), "f"(cf.w) : "memory");
            mbar_arrive(sb + B_COEF);
          }
          mbar_wait(sb + B_COEF, 0);
          SsmCoef co[2];
          co[0] = ssm_powers(sb + SM_GW + (slot - 1) * 1024 + 16 * (16 * w + (lane >> 2)));
          co[1] = ssm_powers(sb + SM_GW + (slot - 1) * 1024 + 16 * (16 * w + (lane >> 2) + 8));
          bar_sync(1 + wg, 256);
          PROF_EV(slot * 4 + 0);
          const float tok = unit_mainloop<1>(acc0, acc1, g0, g1, sb, slot * 10, slot < 2, signal, wg, lane PROF_ARGS);
          PROF_EV(slot * 4 + 1);
          ssm_epilogue(acc0, acc1, co, P.scr, rb, id, tag + 1, w, lane, P.zero, tok);
        } else {
          if (slot > 0) bar_sync(1 + wg, 256);
          PROF_EV(slot * 4 + 0);
          const float tok = unit_mainloop<0>(acc0, acc1, g0, g1, sb, slot * 10, slot < 2, signal, wg, lane PROF_ARGS);
          PROF_EV(slot * 4 + 1);
          unsigned char* tile = P.scr + G_ACT + (size_t)(rb * NFC + id) * CH;
          float v[NCH];
#pragma unroll
          for (int i = 0; i < NCH; i++) v[i] = tok;
          ffn_pieces<true, 8>(acc0, acc1, tile, w, lane, v, P.zero);
        }
        PROF_EV(slot * 4 + 2);
        bar_arrive(3 + wg, 160);
      }
      float acc0[64], acc1[64], g0[4], g1[4];
      unsigned char* tile = P.scr + G_ACT + (size_t)(rb * NFC + (ftype ? 18 : 23) + nt) * CH;
      if (wg == 1) {
        const int slot = nslots - 1;
        bar_sync(2, 256);
        PROF_EV(slot * 4 + 0);
        const float tok = unit_mainloop<0>(acc0, acc1, g0, g1, sb, slot * 10, false, false, 1, lane PROF_ARGS);
        PROF_EV(slot * 4 + 1);
        float v[NCH];
        v[0] = chain(-1.4426950408889634f, tok, P.zero);
        ffn_pieces<false, NPRE>(acc0, acc1, tile, w, lane, v, P.zero);
        PROF_EV(slot * 4 + 2);
      }
      if (ftype) phase2<true>(P, sb, rb, nt, wg, w, lane, acc0, acc1, tile PROF_ARGS);
      else phase2<false>(P, sb, rb, nt, wg, w, lane, acc0, acc1, tile PROF_ARGS);
    }
  }
}

typedef CUresult (*EncodeFn)(CUtensorMap*, CUtensorMapDataType, cuuint32_t, void*, const cuuint64_t*, const cuuint64_t*,
                             const cuuint32_t*, const cuuint32_t*, CUtensorMapInterleave, CUtensorMapSwizzle,
                             CUtensorMapL2promotion, CUtensorMapFloatOOBfill);

void encode(EncodeFn fn, CUtensorMap* m, const void* base, int rank, const cuuint64_t* dims, const cuuint64_t* strides,
            const cuuint32_t* box, CUtensorMapSwizzle swz = CU_TENSOR_MAP_SWIZZLE_128B) {
  const cuuint32_t es[5] = {1, 1, 1, 1, 1};
  fn(m, CU_TENSOR_MAP_DATA_TYPE_BFLOAT16, rank, const_cast<void*>(base), dims, strides, box, es,
     CU_TENSOR_MAP_INTERLEAVE_NONE, swz, CU_TENSOR_MAP_L2_PROMOTION_L2_128B,
     CU_TENSOR_MAP_FLOAT_OOB_FILL_NONE);
}

}

extern "C" void kernel_launch(void* const* d_in, const int* in_sizes, int n_in, void* d_out, int out_size) {
  (void)in_sizes; (void)n_in; (void)out_size;
  static EncodeFn enc = nullptr;
  static int sms = 0;
  static void* scratch = nullptr;
  if (!enc) {
    void* fn = nullptr;
    cudaDriverEntryPointQueryResult qr;
    cudaGetDriverEntryPoint("cuTensorMapEncodeTiled", &fn, cudaEnableDefault, &qr);
    enc = (EncodeFn)fn;
    int dev = 0;
    cudaGetDevice(&dev);
    cudaDeviceGetAttribute(&sms, cudaDevAttrMultiProcessorCount, dev);
    cudaGetSymbolAddress(&scratch, g_scratch);
    cudaFuncSetAttribute(fused_kernel<true>, cudaFuncAttributeMaxDynamicSharedMemorySize, SMEM_BYTES);
    cudaFuncSetAttribute(fused_kernel<false>, cudaFuncAttributeMaxDynamicSharedMemorySize, SMEM_BYTES);
  }
  typedef const __nv_bfloat16* bp;
  Params P;
  const cuuint64_t R = DM * 2;
  {
    const cuuint64_t d[5] = {DM, 2, 4, 16, NRB}, s[4] = {R, 32 * R, 2 * R, 128 * R};
    const cuuint32_t b[5] = {64, 2, 4, 16, 1};
    encode(enc, &P.x, d_in[0], 5, d, s, b);
  }
  {
    const cuuint64_t d[2] = {DM, DM}, s[1] = {R};
    const cuuint32_t b[2] = {64, 64}, bc[2] = {64, 160};
    encode(enc, &P.bre, d_in[3], 2, d, s, b);
    encode(enc, &P.bim, d_in[4], 2, d, s, b);
    encode(enc, &P.cre, d_in[5], 2, d, s, bc);
    encode(enc, &P.cim, d_in[6], 2, d, s, bc);
  }
  {
    const cuuint64_t d[2] = {FF, DM}, s[1] = {FF * 2};
    const cuuint32_t b[2] = {64, 64};
    encode(enc, &P.wg, d_in[10], 2, d, s, b);
    encode(enc, &P.wu, d_in[11], 2, d, s, b);
  }
  {
    cuuint64_t d[5] = {DM, 2, 4, 4, FF / 32};
    const cuuint64_t s[4] = {R, 8 * R, 2 * R, 32 * R};
    const cuuint32_t b[5] = {64, 2, 4, 4, 2};
    encode(enc, &P.wd, d_in[12], 5, d, s, b);
  }
  {
    const cuuint64_t d[2] = {DM, 2048}, s[1] = {R};
    const cuuint32_t b[2] = {168, 32};
    encode(enc, &P.xs, d_in[0], 2, d, s, b, CU_TENSOR_MAP_SWIZZLE_NONE);
  }
  P.scr = (unsigned char*)scratch;
  P.p_x = (const char*)d_in[0];
  P.lre = (bp)d_in[1]; P.lim = (bp)d_in[2]; P.logdt = (bp)d_in[7]; P.dskip = (bp)d_in[8];
  P.gatew = (bp)d_in[13];
  P.p_bre = (const char*)d_in[3]; P.p_bim = (const char*)d_in[4]; P.p_cre = (const char*)d_in[5]; P.p_cim = (const char*)d_in[6];
  P.p_wg = (const char*)d_in[10]; P.p_wu = (const char*)d_in[11]; P.p_wd = (const char*)d_in[12];
  P.out = (float*)d_out;
  P.zero = 0;
  if (sms == 132) fused_kernel<true><<<132, 384, SMEM_BYTES, cudaStreamPerThread>>>(P);
  else fused_kernel<false><<<132, 384, SMEM_BYTES, cudaStreamPerThread>>>(P);
}
```

```cpp
#include <cuda_runtime.h>
#include <cuda_bf16.h>
#include <cuda.h>
#include <stdint.h>

namespace {

constexpr int DM = 640, FF = 1728;
constexpr int NRB = 16;
constexpr int NFC = 27;
constexpr int NCG = 10;
constexpr int CH = 16384;
constexpr int EXTRA_FC = 22;
constexpr int NCH = 3;

constexpr int SM_RES = 0;
constexpr int SM_RING = 10 * CH;
constexpr int ST2 = 40960;
constexpr int SM_XS = 5 * ST2;
constexpr uint32_t SB_LOCAL = 1024;
constexpr int SM_BAR = 14 * CH;
constexpr int B_XFULL = SM_BAR;
constexpr int B_FULL1 = B_XFULL + 80;
constexpr int B_EMPTY1 = B_FULL1 + 32;
constexpr int B_FULL2 = B_EMPTY1 + 32;
constexpr int B_EMPTY2 = B_FULL2 + 40;
constexpr int B_G = B_EMPTY2 + 40;
constexpr int B_PEER = B_G + 8;
constexpr int B_RECV = B_PEER + 8;
constexpr int B_XS = B_RECV + 64;
constexpr int B_COEF = B_XS + 8;
constexpr int B_DONE = B_COEF + 8;
constexpr int B_RECV2 = B_DONE + 8;
constexpr int SM_READY = B_RECV2 + 64;
constexpr int SM_G = SM_BAR + 512;
constexpr int SM_GW = SM_BAR + 1024;
constexpr int SMEM_BYTES = SM_GW + 2048;

constexpr size_t G_EPOCH = 0;
constexpr size_t G_FLAG_ACT = 1024;
constexpr size_t G_FLAG_H = G_FLAG_ACT + 2048;
constexpr size_t G_GATE = G_FLAG_H + 2048;
constexpr size_t G_AGG = G_GATE + 8192;
constexpr size_t G_H = G_AGG + NCG * NRB * 64 * 16 + 3072;
constexpr size_t G_ACT = G_H + (size_t)NRB * NCG * 2 * CH;
static_assert(G_H % 1024 == 0, "tile alignment");
__device__ __align__(1024) unsigned char g_scratch[G_ACT + (size_t)NRB * NFC * CH];

struct Params {
  const char *p_wg, *p_wu;
  unsigned char* scr;
  float* out;
  uint32_t zero;
  const __nv_bfloat16 *lre, *lim, *logdt, *dskip, *gatew;
  const char *p_cre, *p_cim, *p_wd, *p_bre, *p_bim;
  CUtensorMap x, wg, wu, bre, bim, cre, cim, wd, xs;
};

__device__ __forceinline__ uint32_t smem_u32(const void* p) { return (uint32_t)__cvta_generic_to_shared(p); }
__device__ __forceinline__ bool elect_one() {
  uint32_t p;
  asm volatile("{\n.reg .pred p;\nelect.sync _|p, 0xffffffff;\nselp.u32 %0, 1, 0, p;\n}" : "=r"(p));
  return p != 0;
}
__device__ __forceinline__ void mbar_init(uint32_t bar, uint32_t cnt) {
  asm volatile("mbarrier.init.shared::cta.b64 [%0], %1;" ::"r"(bar), "r"(cnt) : "memory");
}
__device__ __forceinline__ void mbar_expect_tx(uint32_t bar, uint32_t bytes) {
  asm volatile("mbarrier.arrive.expect_tx.shared::cta.b64 _, [%0], %1;" ::"r"(bar), "r"(bytes) : "memory");
}
__device__ __forceinline__ void mbar_arrive(uint32_t bar) {
  asm volatile("mbarrier.arrive.shared::cta.b64 _, [%0];" ::"r"(bar) : "memory");
}
__device__ __forceinline__ uint32_t mapa(uint32_t addr, uint32_t cta) {
  uint32_t r;
  asm("mapa.shared::cluster.u32 %0, %1, %2;" : "=r"(r) : "r"(addr), "r"(cta));
  return r;
}
__device__ __forceinline__ void mbar_arrive_remote(uint32_t cluster_bar) {
  asm volatile("mbarrier.arrive.relaxed.cluster.shared::cluster.b64 _, [%0];" ::"r"(cluster_bar) : "memory");
}
__device__ __forceinline__ void mbar_wait(uint32_t bar, uint32_t parity) {
  asm volatile("{\n.reg .pred p;\nW:\nmbarrier.try_wait.parity.shared::cta.b64 p, [%0], %1;\n@p bra D;\nbra W;\nD:\n}"
               ::"r"(bar), "r"(parity) : "memory");
}
__device__ __forceinline__ void mbar_wait_cluster(uint32_t bar, uint32_t parity) {
  asm volatile("{\n.reg .pred p;\nW:\nmbarrier.try_wait.parity.acquire.cluster.shared::cta.b64 p, [%0], %1;\n@p bra D;\nbra W;\nD:\n}"
               ::"r"(bar), "r"(parity) : "memory");
}
__device__ __forceinline__ void mbar_wait_bounded(uint32_t bar, uint32_t parity) {
  asm volatile("{\n.reg .pred p;\n.reg .u32 c;\nmov.u32 c, 0;\n"
               "W:\nmbarrier.try_wait.parity.shared::cta.b64 p, [%0], %1;\n@p bra D;\n"
               "add.u32 c, c, 1;\nsetp.gt.u32 p, c, 131072;\n@p trap;\nbra W;\nD:\n}"
               ::"r"(bar), "r"(parity) : "memory");
}
__device__ __forceinline__ uint32_t mbar_test(uint32_t bar, uint32_t parity) {
  uint32_t ok;
  asm volatile("{\n.reg .pred p;\nmbarrier.test_wait.parity.shared::cta.b64 p, [%1], %2;\nselp.u32 %0, 1, 0, p;\n}"
               : "=r"(ok) : "r"(bar), "r"(parity) : "memory");
  return ok;
}
__device__ __forceinline__ void mbar_arrive_elect(uint32_t bar) {
  asm volatile("{\n.reg .pred p;\nelect.sync _|p, 0xffffffff;\n@p mbarrier.arrive.shared::cta.b64 _, [%0];\n}" ::"r"(bar) : "memory");
}
__device__ __forceinline__ float mbar_arrive_token(uint32_t bar) {
  uint32_t lo;
  asm volatile("{\n.reg .pred p;\n.reg .b64 st;\n.reg .b32 hi;\nmov.b64 st, 0;\nelect.sync _|p, 0xffffffff;\n"
               "@p mbarrier.arrive.shared::cta.b64 st, [%1];\nmov.b64 {%0, hi}, st;\n}" : "=r"(lo) : "r"(bar) : "memory");
  return __uint_as_float(lo);
}
__device__ __forceinline__ void trap_if_over(int n, int limit) {
  asm volatile("{\n.reg .pred p;\nsetp.gt.s32 p, %0, %1;\n@p trap;\n}" ::"r"(n), "r"(limit));
}
__device__ __forceinline__ void bulk_load(uint32_t dst, const void* src, uint32_t bytes, uint32_t bar) {
  asm volatile("cp.async.bulk.shared::cluster.global.mbarrier::complete_tx::bytes [%0], [%1], %2, [%3];"
               ::"r"(dst), "l"(src), "r"(bytes), "r"(bar) : "memory");
}
__device__ __forceinline__ void tma2d(uint32_t dst, const CUtensorMap* m, int c0, int c1, uint32_t bar) {
  asm volatile("cp.async.bulk.tensor.2d.shared::cluster.global.mbarrier::complete_tx::bytes [%0], [%1, {%3, %4}], [%2];"
               ::"r"(dst), "l"(m), "r"(bar), "r"(c0), "r"(c1) : "memory");
}
__device__ __forceinline__ void tma5d(uint32_t dst, const CUtensorMap* m, int c0, int c4, uint32_t bar) {
  asm volatile("cp.async.bulk.tensor.5d.shared::cluster.global.mbarrier::complete_tx::bytes [%0], [%1, {%3, %5, %5, %5, %4}], [%2];"
               ::"r"(dst), "l"(m), "r"(bar), "r"(c0), "r"(c4), "r"(0) : "memory");
}
__device__ __forceinline__ void l2_prefetch(const void* p, uint32_t bytes) {
  asm volatile("cp.async.bulk.prefetch.L2.global [%0], %1;" ::"l"(p), "r"(bytes) : "memory");
}
__device__ __forceinline__ void prefetch_map(const CUtensorMap* m) {
  asm volatile("prefetch.tensormap [%0];" ::"l"(m) : "memory");
}
__device__ __forceinline__ void wg_fence() { asm volatile("wgmma.fence.sync.aligned;" ::: "memory"); }
__device__ __forceinline__ void wg_commit() { asm volatile("wgmma.commit_group.sync.aligned;" ::: "memory"); }
template <int N> __device__ __forceinline__ void wg_wait() { asm volatile("wgmma.wait_group.sync.aligned %0;" ::"n"(N) : "memory"); }
template <int R> __device__ __forceinline__ void fence_regs(float (&d)[R]) {
#pragma unroll
  for (int i = 0; i < R; i++) asm volatile("" : "+f"(d[i])::"memory");
}
__device__ __forceinline__ uint64_t desc_k(uint32_t a16) { return ((uint64_t)0x40000040u << 32) | (uint64_t)(a16 + (1u << 16)); }
__device__ __forceinline__ uint64_t desc_mn(uint32_t a16) { return ((uint64_t)0x40000040u << 32) | (uint64_t)(a16 + (512u << 16)); }
__device__ __forceinline__ uint64_t desc_k64(uint32_t a16) { return ((uint64_t)0x80000020u << 32) | (uint64_t)(a16 + (1u << 16)); }
__device__ __forceinline__ uint64_t desc_mn64(uint32_t a16) { return ((uint64_t)0x80000020u << 32) | (uint64_t)(a16 + (256u << 16)); }
__device__ __forceinline__ void bar_sync(int id, int n) { asm volatile("bar.sync %0, %1;" ::"r"(id), "r"(n) : "memory"); }
__device__ __forceinline__ void bar_arrive(int id, int n) { asm volatile("bar.arrive %0, %1;" ::"r"(id), "r"(n) : "memory"); }
__device__ __forceinline__ uint32_t pack_bf16(float lo, float hi) {
  uint32_t r;
  asm("cvt.rn.bf16x2.f32 %0, %1, %2;" : "=r"(r) : "f"(hi), "f"(lo));
  return r;
}
__device__ __forceinline__ float bf_lo(uint32_t v) { return __uint_as_float(v << 16); }
__device__ __forceinline__ float bf_hi(uint32_t v) { return __uint_as_float(v & 0xFFFF0000u); }
__device__ __forceinline__ void st_v4(void* p, uint32_t a, uint32_t b, uint32_t c, uint32_t d) {
  asm volatile("st.global.v4.b32 [%0], {%1, %2, %3, %4};" ::"l"(p), "r"(a), "r"(b), "r"(c), "r"(d) : "memory");
}
__device__ __forceinline__ float fast_ex2(float x) { float y; asm("ex2.approx.ftz.f32 %0, %1;" : "=f"(y) : "f"(x)); return y; }
__device__ __forceinline__ float fast_rcp(float x) { float y; asm("rcp.approx.ftz.f32 %0, %1;" : "=f"(y) : "f"(x)); return y; }
struct cplx { float r, i; };
__device__ __forceinline__ cplx cmul(cplx a, cplx b) { return {a.r * b.r - a.i * b.i, a.r * b.i + a.i * b.r}; }
__device__ __forceinline__ cplx cfma(cplx a, cplx b, cplx c) {
  return {fmaf(a.r, b.r, fmaf(-a.i, b.i, c.r)), fmaf(a.r, b.i, fmaf(a.i, b.r, c.i))};
}
__device__ __forceinline__ cplx cshfl_up(cplx a, int d) {
  return {__shfl_up_sync(0xffffffffu, a.r, d, 4), __shfl_up_sync(0xffffffffu, a.i, d, 4)};
}

template <int TA, int TB, int O = 0, int R>
__device__ __forceinline__ void wgmma_n8(float (&d)[R], uint64_t da, uint64_t db, int scale_d) {
  asm volatile("{\n.reg .pred p;\nsetp.ne.b32 p, %6, 0;\n"
    "wgmma.mma_async.sync.aligned.m64n8k16.f32.bf16.bf16 {"
    "%0, %1, %2, %3"
    "}, %4, %5, p, 1, 1, %7, %8;\n}\n"
    : "+f"(d[O + 0]), "+f"(d[O + 1]), "+f"(d[O + 2]), "+f"(d[O + 3])
    : "l"(da), "l"(db), "r"(scale_d), "n"(TA), "n"(TB));
}
template <int TA, int TB, int O = 0, int R>
__device__ __forceinline__ void wgmma_n8_z(float (&d)[R], uint64_t da, uint64_t db) {
  asm volatile("{\n.reg .pred p;\nsetp.ne.b32 p, 0, 0;\n"
    "wgmma.mma_async.sync.aligned.m64n8k16.f32.bf16.bf16 {"
    "%0, %1, %2, %3"
    "}, %4, %5, p, 1, 1, %6, %7;\n}\n"
    : "=f"(d[O + 0]), "=f"(d[O + 1]), "=f"(d[O + 2]), "=f"(d[O + 3])
    : "l"(da), "l"(db), "n"(TA), "n"(TB));
}

template <int TA, int TB, int O = 0, int R>
__device__ __forceinline__ void wgmma_n64(float (&d)[R], uint64_t da, uint64_t db, int scale_d) {
  asm volatile("{\n.reg .pred p;\nsetp.ne.b32 p, %34, 0;\n"
    "wgmma.mma_async.sync.aligned.m64n64k16.f32.bf16.bf16 {"
    "%0, %1, %2, %3, %4, %5, %6, %7, %8, %9, %10, %11, %12, %13, %14, %15, "
    "%16, %17, %18, %19, %20, %21, %22, %23, %24, %25, %26, %27, %28, %29, %30, %31"
    "}, %32, %33, p, 1, 1, %35, %36;\n}\n"
    : "+f"(d[O + 0]), "+f"(d[O + 1]), "+f"(d[O + 2]), "+f"(d[O + 3]), "+f"(d[O + 4]), "+f"(d[O + 5]), "+f"(d[O + 6]), "+f"(d[O + 7]),
      "+f"(d[O + 8]), "+f"(d[O + 9]), "+f"(d[O + 10]), "+f"(d[O + 11]), "+f"(d[O + 12]), "+f"(d[O + 13]), "+f"(d[O + 14]), "+f"(d[O + 15]),
      "+f"(d[O + 16]), "+f"(d[O + 17]), "+f"(d[O + 18]), "+f"(d[O + 19]), "+f"(d[O + 20]), "+f"(d[O + 21]), "+f"(d[O + 22]), "+f"(d[O + 23]),
      "+f"(d[O + 24]), "+f"(d[O + 25]), "+f"(d[O + 26]), "+f"(d[O + 27]), "+f"(d[O + 28]), "+f"(d[O + 29]), "+f"(d[O + 30]), "+f"(d[O + 31])
    : "l"(da), "l"(db), "r"(scale_d), "n"(TA), "n"(TB));
}
template <int TA, int TB, int O = 0, int R>
__device__ __forceinline__ void wgmma_n64_z(float (&d)[R], uint64_t da, uint64_t db) {
  asm volatile("{\n.reg .pred p;\nsetp.ne.b32 p, 0, 0;\n"
    "wgmma.mma_async.sync.aligned.m64n64k16.f32.bf16.bf16 {"
    "%0, %1, %2, %3, %4, %5, %6, %7, %8, %9, %10, %11, %12, %13, %14, %15, "
    "%16, %17, %18, %19, %20, %21, %22, %23, %24, %25, %26, %27, %28, %29, %30, %31"
    "}, %32, %33, p, 1, 1, %34, %35;\n}\n"
    : "=f"(d[O + 0]), "=f"(d[O + 1]), "=f"(d[O + 2]), "=f"(d[O + 3]), "=f"(d[O + 4]), "=f"(d[O + 5]), "=f"(d[O + 6]), "=f"(d[O + 7]),
      "=f"(d[O + 8]), "=f"(d[O + 9]), "=f"(d[O + 10]), "=f"(d[O + 11]), "=f"(d[O + 12]), "=f"(d[O + 13]), "=f"(d[O + 14]), "=f"(d[O + 15]),
      "=f"(d[O + 16]), "=f"(d[O + 17]), "=f"(d[O + 18]), "=f"(d[O + 19]), "=f"(d[O + 20]), "=f"(d[O + 21]), "=f"(d[O + 22]), "=f"(d[O + 23]),
      "=f"(d[O + 24]), "=f"(d[O + 25]), "=f"(d[O + 26]), "=f"(d[O + 27]), "=f"(d[O + 28]), "=f"(d[O + 29]), "=f"(d[O + 30]), "=f"(d[O + 31])
    : "l"(da), "l"(db), "n"(TA), "n"(TB));
}

template <int TA, int TB, int O = 0, int R>
__device__ __forceinline__ void wgmma_n96(float (&d)[R], uint64_t da, uint64_t db, int scale_d) {
  asm volatile("{\n.reg .pred p;\nsetp.ne.b32 p, %50, 0;\n"
    "wgmma.mma_async.sync.aligned.m64n96k16.f32.bf16.bf16 {"
    "%0, %1, %2, %3, %4, %5, %6, %7, %8, %9, %10, %11, %12, %13, %14, %15, "
    "%16, %17, %18, %19, %20, %21, %22, %23, %24, %25, %26, %27, %28, %29, %30, %31, "
    "%32, %33, %34, %35, %36, %37, %38, %39, %40, %41, %42, %43, %44, %45, %46, %47"
    "}, %48, %49, p, 1, 1, %51, %52;\n}\n"
    : "+f"(d[O + 0]), "+f"(d[O + 1]), "+f"(d[O + 2]), "+f"(d[O + 3]), "+f"(d[O + 4]), "+f"(d[O + 5]), "+f"(d[O + 6]), "+f"(d[O + 7]),
      "+f"(d[O + 8]), "+f"(d[O + 9]), "+f"(d[O + 10]), "+f"(d[O + 11]), "+f"(d[O + 12]), "+f"(d[O + 13]), "+f"(d[O + 14]), "+f"(d[O + 15]),
      "+f"(d[O + 16]), "+f"(d[O + 17]), "+f"(d[O + 18]), "+f"(d[O + 19]), "+f"(d[O + 20]), "+f"(d[O + 21]), "+f"(d[O + 22]), "+f"(d[O + 23]),
      "+f"(d[O + 24]), "+f"(d[O + 25]), "+f"(d[O + 26]), "+f"(d[O + 27]), "+f"(d[O + 28]), "+f"(d[O + 29]), "+f"(d[O + 30]), "+f"(d[O + 31]),
      "+f"(d[O + 32]), "+f"(d[O + 33]), "+f"(d[O + 34]), "+f"(d[O + 35]), "+f"(d[O + 36]), "+f"(d[O + 37]), "+f"(d[O + 38]), "+f"(d[O + 39]),
      "+f"(d[O + 40]), "+f"(d[O + 41]), "+f"(d[O + 42]), "+f"(d[O + 43]), "+f"(d[O + 44]), "+f"(d[O + 45]), "+f"(d[O + 46]), "+f"(d[O + 47])
    : "l"(da), "l"(db), "r"(scale_d), "n"(TA), "n"(TB));
}
template <int TA, int TB, int O = 0, int R>
__device__ __forceinline__ void wgmma_n96_z(float (&d)[R], uint64_t da, uint64_t db) {
  asm volatile("{\n.reg .pred p;\nsetp.ne.b32 p, 0, 0;\n"
    "wgmma.mma_async.sync.aligned.m64n96k16.f32.bf16.bf16 {"
    "%0, %1, %2, %3, %4, %5, %6, %7, %8, %9, %10, %11, %12, %13, %14, %15, "
    "%16, %17, %18, %19, %20, %21, %22, %23, %24, %25, %26, %27, %28, %29, %30, %31, "
    "%32, %33, %34, %35, %36, %37, %38, %39, %40, %41, %42, %43, %44, %45, %46, %47"
    "}, %48, %49, p, 1, 1, %50, %51;\n}\n"
    : "=f"(d[O + 0]), "=f"(d[O + 1]), "=f"(d[O + 2]), "=f"(d[O + 3]), "=f"(d[O + 4]), "=f"(d[O + 5]), "=f"(d[O + 6]), "=f"(d[O + 7]),
      "=f"(d[O + 8]), "=f"(d[O + 9]), "=f"(d[O + 10]), "=f"(d[O + 11]), "=f"(d[O + 12]), "=f"(d[O + 13]), "=f"(d[O + 14]), "=f"(d[O + 15]),
      "=f"(d[O + 16]), "=f"(d[O + 17]), "=f"(d[O + 18]), "=f"(d[O + 19]), "=f"(d[O + 20]), "=f"(d[O + 21]), "=f"(d[O + 22]), "=f"(d[O + 23]),
      "=f"(d[O + 24]), "=f"(d[O + 25]), "=f"(d[O + 26]), "=f"(d[O + 27]), "=f"(d[O + 28]), "=f"(d[O + 29]), "=f"(d[O + 30]), "=f"(d[O + 31]),
      "=f"(d[O + 32]), "=f"(d[O + 33]), "=f"(d[O + 34]), "=f"(d[O + 35]), "=f"(d[O + 36]), "=f"(d[O + 37]), "=f"(d[O + 38]), "=f"(d[O + 39]),
      "=f"(d[O + 40]), "=f"(d[O + 41]), "=f"(d[O + 42]), "=f"(d[O + 43]), "=f"(d[O + 44]), "=f"(d[O + 45]), "=f"(d[O + 46]), "=f"(d[O + 47])
    : "l"(da), "l"(db), "n"(TA), "n"(TB));
}

template <int TA, int TB, int O = 0, int R>
__device__ __forceinline__ void wgmma_n128(float (&d)[R], uint64_t da, uint64_t db, int scale_d) {
  asm volatile("{\n.reg .pred p;\nsetp.ne.b32 p, %66, 0;\n"
    "wgmma.mma_async.sync.aligned.m64n128k16.f32.bf16.bf16 {"
    "%0, %1, %2, %3, %4, %5, %6, %7, %8, %9, %10, %11, %12, %13, %14, %15, "
    "%16, %17, %18, %19, %20, %21, %22, %23, %24, %25, %26, %27, %28, %29, %30, %31, "
    "%32, %33, %34, %35, %36, %37, %38, %39, %40, %41, %42, %43, %44, %45, %46, %47, "
    "%48, %49, %50, %51, %52, %53, %54, %55, %56, %57, %58, %59, %60, %61, %62, %63"
    "}, %64, %65, p, 1, 1, %67, %68;\n}\n"
    : "+f"(d[O + 0]), "+f"(d[O + 1]), "+f"(d[O + 2]), "+f"(d[O + 3]), "+f"(d[O + 4]), "+f"(d[O + 5]), "+f"(d[O + 6]), "+f"(d[O + 7]),
      "+f"(d[O + 8]), "+f"(d[O + 9]), "+f"(d[O + 10]), "+f"(d[O + 11]), "+f"(d[O + 12]), "+f"(d[O + 13]), "+f"(d[O + 14]), "+f"(d[O + 15]),
      "+f"(d[O + 16]), "+f"(d[O + 17]), "+f"(d[O + 18]), "+f"(d[O + 19]), "+f"(d[O + 20]), "+f"(d[O + 21]), "+f"(d[O + 22]), "+f"(d[O + 23]),
      "+f"(d[O + 24]), "+f"(d[O + 25]), "+f"(d[O + 26]), "+f"(d[O + 27]), "+f"(d[O + 28]), "+f"(d[O + 29]), "+f"(d[O + 30]), "+f"(d[O + 31]),
      "+f"(d[O + 32]), "+f"(d[O + 33]), "+f"(d[O + 34]), "+f"(d[O + 35]), "+f"(d[O + 36]), "+f"(d[O + 37]), "+f"(d[O + 38]), "+f"(d[O + 39]),
      "+f"(d[O + 40]), "+f"(d[O + 41]), "+f"(d[O + 42]), "+f"(d[O + 43]), "+f"(d[O + 44]), "+f"(d[O + 45]), "+f"(d[O + 46]), "+f"(d[O + 47]),
      "+f"(d[O + 48]), "+f"(d[O + 49]), "+f"(d[O + 50]), "+f"(d[O + 51]), "+f"(d[O + 52]), "+f"(d[O + 53]), "+f"(d[O + 54]), "+f"(d[O + 55]),
      "+f"(d[O + 56]), "+f"(d[O + 57]), "+f"(d[O + 58]), "+f"(d[O + 59]), "+f"(d[O + 60]), "+f"(d[O + 61]), "+f"(d[O + 62]), "+f"(d[O + 63])
    : "l"(da), "l"(db), "r"(scale_d), "n"(TA), "n"(TB));
}
template <int TA, int TB, int O = 0, int R>
__device__ __forceinline__ void wgmma_n128_z(float (&d)[R], uint64_t da, uint64_t db) {
  asm volatile("{\n.reg .pred p;\nsetp.ne.b32 p, 0, 0;\n"
    "wgmma.mma_async.sync.aligned.m64n128k16.f32.bf16.bf16 {"
    "%0, %1, %2, %3, %4, %5, %6, %7, %8, %9, %10, %11, %12, %13, %14, %15, "
    "%16, %17, %18, %19, %20, %21, %22, %23, %24, %25, %26, %27, %28, %29, %30, %31, "
    "%32, %33, %34, %35, %36, %37, %38, %39, %40, %41, %42, %43, %44, %45, %46, %47, "
    "%48, %49, %50, %51, %52, %53, %54, %55, %56, %57, %58, %59, %60, %61, %62, %63"
    "}, %64, %65, p, 1, 1, %66, %67;\n}\n"
    : "=f"(d[O + 0]), "=f"(d[O + 1]), "=f"(d[O + 2]), "=f"(d[O + 3]), "=f"(d[O + 4]), "=f"(d[O + 5]), "=f"(d[O + 6]), "=f"(d[O + 7]),
      "=f"(d[O + 8]), "=f"(d[O + 9]), "=f"(d[O + 10]), "=f"(d[O + 11]), "=f"(d[O + 12]), "=f"(d[O + 13]), "=f"(d[O + 14]), "=f"(d[O + 15]),
      "=f"(d[O + 16]), "=f"(d[O + 17]), "=f"(d[O + 18]), "=f"(d[O + 19]), "=f"(d[O + 20]), "=f"(d[O + 21]), "=f"(d[O + 22]), "=f"(d[O + 23]),
      "=f"(d[O + 24]), "=f"(d[O + 25]), "=f"(d[O + 26]), "=f"(d[O + 27]), "=f"(d[O + 28]), "=f"(d[O + 29]), "=f"(d[O + 30]), "=f"(d[O + 31]),
      "=f"(d[O + 32]), "=f"(d[O + 33]), "=f"(d[O + 34]), "=f"(d[O + 35]), "=f"(d[O + 36]), "=f"(d[O + 37]), "=f"(d[O + 38]), "=f"(d[O + 39]),
      "=f"(d[O + 40]), "=f"(d[O + 41]), "=f"(d[O + 42]), "=f"(d[O + 43]), "=f"(d[O + 44]), "=f"(d[O + 45]), "=f"(d[O + 46]), "=f"(d[O + 47]),
      "=f"(d[O + 48]), "=f"(d[O + 49]), "=f"(d[O + 50]), "=f"(d[O + 51]), "=f"(d[O + 52]), "=f"(d[O + 53]), "=f"(d[O + 54]), "=f"(d[O + 55]),
      "=f"(d[O + 56]), "=f"(d[O + 57]), "=f"(d[O + 58]), "=f"(d[O + 59]), "=f"(d[O + 60]), "=f"(d[O + 61]), "=f"(d[O + 62]), "=f"(d[O + 63])
    : "l"(da), "l"(db), "n"(TA), "n"(TB));
}

template <int TA, int TB, int O = 0, int R>
__device__ __forceinline__ void wgmma_n160(float (&d)[R], uint64_t da, uint64_t db, int scale_d) {
  asm volatile("{\n.reg .pred p;\nsetp.ne.b32 p, %82, 0;\n"
    "wgmma.mma_async.sync.aligned.m64n160k16.f32.bf16.bf16 {"
    "%0, %1, %2, %3, %4, %5, %6, %7, %8, %9, %10, %11, %12, %13, %14, %15, "
    "%16, %17, %18, %19, %20, %21, %22, %23, %24, %25, %26, %27, %28, %29, %30, %31, "
    "%32, %33, %34, %35, %36, %37, %38, %39, %40, %41, %42, %43, %44, %45, %46, %47, "
    "%48, %49, %50, %51, %52, %53, %54, %55, %56, %57, %58, %59, %60, %61, %62, %63, "
    "%64, %65, %66, %67, %68, %69, %70, %71, %72, %73, %74, %75, %76, %77, %78, %79"
    "}, %80, %81, p, 1, 1, %83, %84;\n}\n"
    : "+f"(d[O + 0]), "+f"(d[O + 1]), "+f"(d[O + 2]), "+f"(d[O + 3]), "+f"(d[O + 4]), "+f"(d[O + 5]), "+f"(d[O + 6]), "+f"(d[O + 7]),
      "+f"(d[O + 8]), "+f"(d[O + 9]), "+f"(d[O + 10]), "+f"(d[O + 11]), "+f"(d[O + 12]), "+f"(d[O + 13]), "+f"(d[O + 14]), "+f"(d[O + 15]),
      "+f"(d[O + 16]), "+f"(d[O + 17]), "+f"(d[O + 18]), "+f"(d[O + 19]), "+f"(d[O + 20]), "+f"(d[O + 21]), "+f"(d[O + 22]), "+f"(d[O + 23]),
      "+f"(d[O + 24]), "+f"(d[O + 25]), "+f"(d[O + 26]), "+f"(d[O + 27]), "+f"(d[O + 28]), "+f"(d[O + 29]), "+f"(d[O + 30]), "+f"(d[O + 31]),
      "+f"(d[O + 32]), "+f"(d[O + 33]), "+f"(d[O + 34]), "+f"(d[O + 35]), "+f"(d[O + 36]), "+f"(d[O + 37]), "+f"(d[O + 38]), "+f"(d[O + 39]),
      "+f"(d[O + 40]), "+f"(d[O + 41]), "+f"(d[O + 42]), "+f"(d[O + 43]), "+f"(d[O + 44]), "+f"(d[O + 45]), "+f"(d[O + 46]), "+f"(d[O + 47]),
      "+f"(d[O + 48]), "+f"(d[O + 49]), "+f"(d[O + 50]), "+f"(d[O + 51]), "+f"(d[O + 52]), "+f"(d[O + 53]), "+f"(d[O + 54]), "+f"(d[O + 55]),
      "+f"(d[O + 56]), "+f"(d[O + 57]), "+f"(d[O + 58]), "+f"(d[O + 59]), "+f"(d[O + 60]), "+f"(d[O + 61]), "+f"(d[O + 62]), "+f"(d[O + 63]),
      "+f"(d[O + 64]), "+f"(d[O + 65]), "+f"(d[O + 66]), "+f"(d[O + 67]), "+f"(d[O + 68]), "+f"(d[O + 69]), "+f"(d[O + 70]), "+f"(d[O + 71]),
      "+f"(d[O + 72]), "+f"(d[O + 73]), "+f"(d[O + 74]), "+f"(d[O + 75]), "+f"(d[O + 76]), "+f"(d[O + 77]), "+f"(d[O + 78]), "+f"(d[O + 79])
    : "l"(da), "l"(db), "r"(scale_d), "n"(TA), "n"(TB));
}
template <int TA, int TB, int O = 0, int R>
__device__ __forceinline__ void wgmma_n160_z(float (&d)[R], uint64_t da, uint64_t db) {
  asm volatile("{\n.reg .pred p;\nsetp.ne.b32 p, 0, 0;\n"
    "wgmma.mma_async.sync.aligned.m64n160k16.f32.bf16.bf16 {"
    "%0, %1, %2, %3, %4, %5, %6, %7, %8, %9, %10, %11, %12, %13, %14, %15, "
    "%16, %17, %18, %19, %20, %21, %22, %23, %24, %25, %26, %27, %28, %29, %30, %31, "
    "%32, %33, %34, %35, %36, %37, %38, %39, %40, %41, %42, %43, %44, %45, %46, %47, "
    "%48, %49, %50, %51, %52, %53, %54, %55, %56, %57, %58, %59, %60, %61, %62, %63, "
    "%64, %65, %66, %67, %68, %69, %70, %71, %72, %73, %74, %75, %76, %77, %78, %79"
    "}, %80, %81, p, 1, 1, %82, %83;\n}\n"
    : "=f"(d[O + 0]), "=f"(d[O + 1]), "=f"(d[O + 2]), "=f"(d[O + 3]), "=f"(d[O + 4]), "=f"(d[O + 5]), "=f"(d[O + 6]), "=f"(d[O + 7]),
      "=f"(d[O + 8]), "=f"(d[O + 9]), "=f"(d[O + 10]), "=f"(d[O + 11]), "=f"(d[O + 12]), "=f"(d[O + 13]), "=f"(d[O + 14]), "=f"(d[O + 15]),
      "=f"(d[O + 16]), "=f"(d[O + 17]), "=f"(d[O + 18]), "=f"(d[O + 19]), "=f"(d[O + 20]), "=f"(d[O + 21]), "=f"(d[O + 22]), "=f"(d[O + 23]),
      "=f"(d[O + 24]), "=f"(d[O + 25]), "=f"(d[O + 26]), "=f"(d[O + 27]), "=f"(d[O + 28]), "=f"(d[O + 29]), "=f"(d[O + 30]), "=f"(d[O + 31]),
      "=f"(d[O + 32]), "=f"(d[O + 33]), "=f"(d[O + 34]), "=f"(d[O + 35]), "=f"(d[O + 36]), "=f"(d[O + 37]), "=f"(d[O + 38]), "=f"(d[O + 39]),
      "=f"(d[O + 40]), "=f"(d[O + 41]), "=f"(d[O + 42]), "=f"(d[O + 43]), "=f"(d[O + 44]), "=f"(d[O + 45]), "=f"(d[O + 46]), "=f"(d[O + 47]),
      "=f"(d[O + 48]), "=f"(d[O + 49]), "=f"(d[O + 50]), "=f"(d[O + 51]), "=f"(d[O + 52]), "=f"(d[O + 53]), "=f"(d[O + 54]), "=f"(d[O + 55]),
      "=f"(d[O + 56]), "=f"(d[O + 57]), "=f"(d[O + 58]), "=f"(d[O + 59]), "=f"(d[O + 60]), "=f"(d[O + 61]), "=f"(d[O + 62]), "=f"(d[O + 63]),
      "=f"(d[O + 64]), "=f"(d[O + 65]), "=f"(d[O + 66]), "=f"(d[O + 67]), "=f"(d[O + 68]), "=f"(d[O + 69]), "=f"(d[O + 70]), "=f"(d[O + 71]),
      "=f"(d[O + 72]), "=f"(d[O + 73]), "=f"(d[O + 74]), "=f"(d[O + 75]), "=f"(d[O + 76]), "=f"(d[O + 77]), "=f"(d[O + 78]), "=f"(d[O + 79])
    : "l"(da), "l"(db), "n"(TA), "n"(TB));
}


__device__ __forceinline__ unsigned load_epoch(const Params& P, int role) {
  unsigned tag;
  asm volatile("ld.relaxed.gpu.global.u32 %0, [%1];" : "=r"(tag) : "l"(P.scr + G_EPOCH + 4 * role) : "memory");
  return tag;
}

__device__ __forceinline__ int unit_of(int ftype, int nt, int s, bool& ssm) {
  const int c = ftype * 4 + nt;
  ssm = false;
  if (s == 0) return c;
  if (s == 1) { ssm = true; return c; }
  if (s == 2) {
    if (!ftype) return 10 + nt;
    ssm = nt < 2;
    return ssm ? 8 + nt : 6 + nt;
  }
  if (s == 3) return 14 + c;
  return 23 + nt;
}

template <int MODE, bool ZERO>
__device__ __forceinline__ void unit_mma(float (&acc0)[64], float (&acc1)[64], float (&g0)[4], float (&g1)[4], uint32_t xa,
                                         uint32_t wa, uint32_t ga, int kk) {
  if (MODE == 1) {
    const uint64_t db = desc_k(xa + kk * 2);
    if (ZERO) { wgmma_n128_z<0, 0>(acc0, desc_k(wa), db); wgmma_n128_z<0, 0>(acc1, desc_k(wa + 512), db); }
    else { wgmma_n128<0, 0>(acc0, desc_k(wa + kk * 2), db, 1); wgmma_n128<0, 0>(acc1, desc_k(wa + 512 + kk * 2), db, 1); }
  } else {
    const uint64_t db = desc_mn(wa + kk * 128);
    if (ZERO) { wgmma_n128_z<0, 1>(acc0, desc_k(xa), db); wgmma_n128_z<0, 1>(acc1, desc_k(xa + 512), db); }
    else { wgmma_n128<0, 1>(acc0, desc_k(xa + kk * 2), db, 1); wgmma_n128<0, 1>(acc1, desc_k(xa + 512 + kk * 2), db, 1); }
    if (MODE == 2) {
      const uint64_t dg = ((uint64_t)1 << 32) | (uint64_t)(ga + kk * 2 + (1u << 16));
      if (ZERO) { wgmma_n8_z<0, 0>(g0, desc_k(xa), dg); wgmma_n8_z<0, 0>(g1, desc_k(xa + 512), dg); }
      else { wgmma_n8<0, 0>(g0, desc_k(xa + kk * 2), dg, 1); wgmma_n8<0, 0>(g1, desc_k(xa + 512 + kk * 2), dg, 1); }
    }
  }
}
template <int MODE>
__device__ __forceinline__ void unit_fence(float (&acc0)[64], float (&acc1)[64], float (&g0)[4], float (&g1)[4]) {
  fence_regs(acc0); fence_regs(acc1);
  if (MODE == 2) { fence_regs(g0); fence_regs(g1); }
}
template <int MODE, bool K0>
__device__ __forceinline__ uint32_t unit_kstep(float (&acc0)[64], float (&acc1)[64], float (&g0)[4], float (&g1)[4], uint32_t sb,
                                               int k, uint32_t& s, uint32_t& ph, bool first) {
  constexpr uint32_t sb16 = SB_LOCAL >> 4;
  const uint32_t res = sb16 + (SM_RES >> 4) + k * (CH >> 4), ring = sb16 + (SM_RING >> 4) + s * (CH >> 4);
  const uint32_t xa = MODE == 2 ? ring : res, wa = MODE == 2 ? res : ring, ga = sb16 + (SM_GW >> 4) + k * 8;
  const uint32_t sp = (s + 3) & 3;
  s = (s + 1) & 3;
  ph ^= (s == 0);
  if (!K0) unit_fence<MODE>(acc0, acc1, g0, g1);
  wg_fence();
  unit_mma<MODE, K0>(acc0, acc1, g0, g1, xa, wa, ga, 0);
  unit_mma<MODE, false>(acc0, acc1, g0, g1, xa, wa, ga, 1);
  wg_commit();
  if (!K0) {
    wg_wait<1>();
    mbar_arrive_elect(sb + B_EMPTY1 + 8 * sp);
  }
  uint32_t ok = mbar_test(sb + B_FULL1 + 8 * s, ph);
  if (first) ok &= mbar_test(sb + B_XFULL + 8 * (k + 1), 0);
  unit_fence<MODE>(acc0, acc1, g0, g1);
  wg_fence();
  unit_mma<MODE, false>(acc0, acc1, g0, g1, xa, wa, ga, 2);
  unit_mma<MODE, false>(acc0, acc1, g0, g1, xa, wa, ga, 3);
  wg_commit();
  unit_fence<MODE>(acc0, acc1, g0, g1);
  return ok;
}
template <int MODE>
__device__ __forceinline__ float unit_mainloop(float (&acc0)[64], float (&acc1)[64], float (&g0)[4], float (&g1)[4], uint32_t sb,
                                              int it0, bool first, bool signal, int wg, int lane) {
  uint32_t s = it0 & 3, ph = (it0 >> 2) & 1;
  if (first) mbar_wait(sb + B_XFULL, 0);
  mbar_wait(sb + B_FULL1 + 8 * s, ph);
  uint32_t ok = unit_kstep<MODE, true>(acc0, acc1, g0, g1, sb, 0, s, ph, first);
#pragma unroll 1
  for (int k = 1; k < 10; k++) {
    if (!ok) {
      if (first) mbar_wait(sb + B_XFULL + 8 * k, 0);
      mbar_wait(sb + B_FULL1 + 8 * s, ph);
    }
    ok = unit_kstep<MODE, false>(acc0, acc1, g0, g1, sb, k, s, ph, first);
  }
  if (signal) bar_arrive(1 + (wg ^ 1), 256);
  wg_wait<0>();
  unit_fence<MODE>(acc0, acc1, g0, g1);
  return mbar_arrive_token(sb + B_EMPTY1 + 8 * ((s + 3) & 3));
}

__device__ __forceinline__ void block_end(uint32_t zero) {
  asm volatile("{\n.reg .pred p;\n.reg .u32 c;\nsetp.eq.u32 p, %0, 0;\n@p bra D;\n"
               "L:\nmov.u32 c, %%clock;\nsetp.lt.u32 p, c, %0;\n@p bra L;\nD:\n}" ::"r"(zero) : "memory");
}

__device__ __forceinline__ float chain(float x, float y, uint32_t zero) {
  return __uint_as_float(__float_as_uint(x) | (__float_as_uint(y) & zero));
}

template <bool PACED, int PIECE>
__device__ __forceinline__ void ffn_piece(const float (&a0)[64], const float (&a1)[64], unsigned char* tile, int w, int lane,
                                          float (&v)[NCH], uint32_t zero) {
  constexpr int mh = PIECE >> 2, hi = (PIECE >> 1) & 1, h = PIECE & 1;
  const int q = lane & 3, r = lane >> 2;
  const int m7 = 4 * (w & 1) + 2 * hi + (r & 1);
  const int m = (2 * mh + (w >> 1)) * 32 + (r >> 1) * 8 + m7;
  uint32_t p[4];
#pragma unroll
  for (int j = 0; j < 4; j++) {
    float o[2];
#pragma unroll
    for (int e = 0; e < 2; e++) {
      const int i = 4 * (4 * h + j) + 2 * hi + e, c = (8 * PIECE + 2 * j + e) % NCH;
      const float g = mh ? a1[i] : a0[i], u = mh ? a1[32 + i] : a0[32 + i];
      const float sg = fast_rcp(1.0f + fast_ex2(g * (PACED ? chain(-1.4426950408889634f, v[c], zero) : v[0])));
      o[e] = (g * sg) * u;
      if (PACED) v[c] = o[e];
    }
    p[j] = pack_bf16(o[0], o[1]);
  }
  st_v4(tile + h * 8192 + m * 64 + ((q ^ (m7 >> 1)) << 4), p[0], p[1], p[2], p[3]);
}
template <bool PACED, int N, int I = 0>
__device__ __forceinline__ void ffn_pieces(const float (&a0)[64], const float (&a1)[64], unsigned char* tile, int w, int lane,
                                           float (&v)[NCH], uint32_t zero) {
  if constexpr (I < N) {
    ffn_piece<PACED, I>(a0, a1, tile, w, lane, v, zero);
    if (PACED && I + 1 < N) block_end(zero);
    ffn_pieces<PACED, N, I + 1>(a0, a1, tile, w, lane, v, zero);
  }
}

struct SsmCoef { cplx lam, c, l32, l64, c1, m4, mq, lq; };
__device__ __forceinline__ float4 ssm_coef(const Params& P, int p) {
  const float lr = __bfloat162float(P.lre[p]), li = __bfloat162float(P.lim[p]);
  const float dt = __bfloat162float(__float2bfloat16_rn(expf(__bfloat162float(P.logdt[p]))));
  float sn, cs;
  sincospif(dt * li * 0.31830988618379067f, &sn, &cs);
  const float ex = expf(dt * lr);
  const float nr = ex * cs - 1.0f, ni = ex * sn, den = 1.0f / (lr * lr + li * li);
  return make_float4(ex * cs, ex * sn, (nr * lr + ni * li) * den, (ni * lr - nr * li) * den);
}
__device__ __forceinline__ SsmCoef ssm_powers(uint32_t addr, int q) {
  SsmCoef o;
  asm volatile("ld.shared.v4.f32 {%0, %1, %2, %3}, [%4];" : "=f"(o.lam.r), "=f"(o.lam.i), "=f"(o.c.r), "=f"(o.c.i) : "r"(addr) : "memory");
  cplx t = o.lam;
#pragma unroll
  for (int i = 0; i < 5; i++) t = cmul(t, t);
  o.l32 = t;
  o.l64 = cmul(t, t);
  const cplx mu = cmul(o.l64, o.l64), mu2 = cmul(mu, mu), one = {1.f, 0.f};
  o.m4 = cmul(mu2, mu2);
  o.mq = cmul((q & 1) ? mu : one, (q & 2) ? mu2 : one);
  o.lq = cmul(cmul((q & 1) ? o.l32 : one, (q & 2) ? o.l64 : one), o.c);
  const cplx nil = {0.f, 0.f};
  o.c1 = q >= 1 ? o.c : nil;
  o.l32 = q >= 1 ? o.l32 : nil;
  o.l64 = q >= 2 ? o.l64 : nil;
  return o;
}

__device__ __forceinline__ void agg_load(unsigned long long& a, unsigned long long& b, const void* p, int valid) {
  asm volatile("{\n.reg .pred p;\nsetp.ne.s32 p, %3, 0;\n@p ld.relaxed.gpu.global.v2.b64 {%0, %1}, [%2];\n}"
               : "+l"(a), "+l"(b) : "l"(p), "r"(valid) : "memory");
}

__device__ __forceinline__ void ssm_epilogue(const float (&vr)[64], const float (&vi)[64], const SsmCoef (&co)[2], unsigned char* scr, int rb,
                                             int cg, unsigned tag, int w, int lane, uint32_t zero, float prev) {
  const int q = lane & 3, r = lane >> 2;
  char* agg = (char*)scr + G_AGG + ((cg * NRB + rb) * 64 + 16 * w + r) * 16;
  cplx h0[2];
#pragma unroll
  for (int hi = 0; hi < 2; hi++) {
    const cplx lam = {chain(co[hi].lam.r, prev, zero), chain(co[hi].lam.i, prev, zero)};
    cplx s = {vr[2 * hi], vi[2 * hi]};
#pragma unroll
    for (int t = 1; t < 32; t++) {
      const int i = 4 * (t >> 1) + 2 * hi + (t & 1);
      s = cfma(lam, s, cplx{vr[i], vi[i]});
    }
    cplx y = cshfl_up(s, 1);
    s = cfma(co[hi].l32, y, s);
    y = cshfl_up(s, 2);
    s = cfma(co[hi].l64, y, s);
    const unsigned long long a = ((unsigned long long)tag << 32) | __float_as_uint(s.r);
    const unsigned long long b = ((unsigned long long)tag << 32) | __float_as_uint(s.i);
    asm volatile("{\n.reg .pred p;\nsetp.eq.s32 p, %3, 3;\n@p st.relaxed.gpu.global.v2.b64 [%0], {%1, %2};\n}"
                 ::"l"(agg + 128 * hi), "l"(a), "l"(b), "r"(q) : "memory");
    block_end(zero);
    y = cshfl_up(s, 1);
    h0[hi] = cmul(co[hi].c1, y);
    prev = s.i;
  }
  const int nv = rb - q;
  const char* src = agg - (1 + q) * 1024;
  unsigned long long ea[2][4], eb[2][4];
  float wr[64], wn[64], cr;
#pragma unroll
  for (int t = 0; t < 64; t++) {
    if (t == 6 || t == 48) {
      const int h2 = t == 48;
      const char* sp = src + (__float_as_uint(prev) & zero);
#pragma unroll
      for (int m = 0; m < 4; m++)
        asm volatile("{\n.reg .pred p;\nsetp.ne.s32 p, %3, 0;\n@p ld.relaxed.gpu.global.v2.b64 {%0, %1}, [%2];\n}"
                     : "=l"(ea[h2][m]), "=l"(eb[h2][m]) : "l"(sp + 128 * h2 - 4096 * m), "r"((int)(4 * m < nv)) : "memory");
      block_end(zero);
    }
    const int hi = t >> 5, i = 4 * ((t & 31) >> 1) + 2 * hi + (t & 1);
    if (t % 2 == 0) cr = chain(co[hi].c.r, prev, zero);
    const float ci = co[hi].c.i, a = vr[i], b = vi[i], ta = cr * a;
    wr[i] = fmaf(-ci, b, ta);
    wn[i] = fmaf(-ci, a, -cr * b);
    prev = ta;
  }
  unsigned char* tile = scr + G_H + (size_t)((rb * NCG + cg) * 2) * CH + (16 * w + r) * 64 + ((q ^ (r >> 1)) << 4);
#pragma unroll
  for (int hi = 0; hi < 2; hi++) {
    int spin = 0;
    while (true) {
      unsigned bad = 0;
#pragma unroll
      for (int m = 0; m < 4; m++)
        if (4 * m < nv) bad |= ((unsigned)(ea[hi][m] >> 32) ^ tag) | ((unsigned)(eb[hi][m] >> 32) ^ tag);
      if (__all_sync(0xffffffffu, bad == 0)) break;
#pragma unroll
      for (int m = 0; m < 4; m++) agg_load(ea[hi][m], eb[hi][m], src + 128 * hi - 4096 * m, 4 * m < nv);
      trap_if_over(++spin, 1 << 21);
    }
    cplx a = {0.f, 0.f};
#pragma unroll
    for (int m = 3; m >= 0; m--)
      if (4 * m < nv) a = cfma(co[hi].m4, a, cplx{__uint_as_float((unsigned)ea[hi][m]), __uint_as_float((unsigned)eb[hi][m])});
    a = cmul(a, co[hi].mq);
    a.r += __shfl_xor_sync(0xffffffffu, a.r, 1); a.i += __shfl_xor_sync(0xffffffffu, a.i, 1);
    a.r += __shfl_xor_sync(0xffffffffu, a.r, 2); a.i += __shfl_xor_sync(0xffffffffu, a.i, 2);
    a = cfma(co[hi].lq, a, h0[hi]);
    const cplx lam = co[hi].lam;
    float hr = a.r, hn = -a.i;
#pragma unroll
    for (int i8 = 0; i8 < 4; i8++) {
      uint32_t pr[4], pi[4];
#pragma unroll
      for (int jj = 0; jj < 4; jj++) {
        float fr[2], fn[2];
#pragma unroll
        for (int e = 0; e < 2; e++) {
          const int i = 4 * (4 * i8 + jj) + 2 * hi + e;
          const float nr = fmaf(lam.r, hr, fmaf(lam.i, hn, wr[i]));
          const float nn = fmaf(lam.r, hn, fmaf(-lam.i, hr, wn[i]));
          fr[e] = hr = nr; fn[e] = hn = nn;
        }
        pr[jj] = pack_bf16(fr[0], fr[1]);
        pi[jj] = pack_bf16(fn[0], fn[1]);
      }
      unsigned char* p = tile + i8 * 4096 + hi * 512;
      st_v4(p, pr[0], pr[1], pr[2], pr[3]);
      st_v4(p + CH, pi[0], pi[1], pi[2], pi[3]);
      if (i8 < 3) block_end(zero);
    }
  }
}

__device__ __forceinline__ void ldmatrix4(uint32_t* r, uint32_t addr) {
  asm volatile("ldmatrix.sync.aligned.m8n8.x4.shared.b16 {%0, %1, %2, %3}, [%4];"
               : "=r"(r[0]), "=r"(r[1]), "=r"(r[2]), "=r"(r[3]) : "r"(addr) : "memory");
}

template <bool F, bool K0, int NR>
__device__ __forceinline__ void p2_mma(float (&acc)[NR], float (&acb)[32], uint32_t a, uint32_t b, uint32_t lbo96) {
  if (!K0) { fence_regs(acc); if (F) fence_regs(acb); }
  wg_fence();
#pragma unroll
  for (int kk = 0; kk < 4; kk++) {
    if constexpr (F) {
      const uint64_t d96 = ((uint64_t)0x40000040u << 32) | (uint64_t)(b + kk * 128 + lbo96);
      const uint64_t da = desc_k64(a + (kk >> 1) * 512 + (kk & 1) * 2);
      if (K0 && kk == 0) { wgmma_n96_z<0, 1>(acc, da, d96); wgmma_n64_z<0, 1>(acb, da, desc_mn(b + 512)); }
      else { wgmma_n96<0, 1>(acc, da, d96, 1); wgmma_n64<0, 1>(acb, da, desc_mn(b + 512 + kk * 128), 1); }
    } else {
      if (K0 && kk == 0) wgmma_n160_z<1, 0>(acc, desc_mn64(a), desc_k(b));
      else wgmma_n160<1, 0>(acc, desc_mn64(a + kk * 64), desc_k(b + kk * 2), 1);
    }
  }
  wg_commit();
  fence_regs(acc);
  if (F) fence_regs(acb);
}

template <bool F>
__device__ __forceinline__ void phase2(const Params& P, uint32_t sb, int rb, int nt, int wg, int w, int lane,
                                       const float (&u1)[64], unsigned char* tile) {
  constexpr int NK = F ? NFC : 2 * NCG;
  constexpr int NA = 2;
  const int q = lane & 3, r = lane >> 2, warp = wg * 4 + w;
  if (elect_one()) { mbar_expect_tx(sb + B_RECV + 8 * warp, 512 * NA); mbar_expect_tx(sb + B_RECV2 + 8 * warp, 512 * (5 - NA)); }
  asm volatile("barrier.cluster.wait.acquire.aligned;" ::: "memory");
  const uint32_t peer = F ? 0 : 1;
  constexpr uint32_t sb16 = SB_LOCAL >> 4;
  float acc[F ? 48 : 80], acb[32];
  const int rot = (F && (nt & 1)) ? 1 : 0;
  const uint32_t lbo96 = (1024u + 4u * rot) << 16, aoff = wg * (F ? 256 : 512);
#define ACC(i) (F && (i) >= 48 ? acb[(i) >= 48 ? (i) - 48 : 0] : acc[F && (i) >= 48 ? 0 : (i)])
  mbar_wait(sb + B_FULL2, 0);
  p2_mma<F, true>(acc, acb, sb16 + aoff, sb16 + (CH >> 4), lbo96);
  float v[NCH] = {};
#define P2_STEP_WITH_PIECE(K)                                                                                          \
  if (wg == 1) ffn_piece<true, 4 + (K)>(u1, u1, tile, w, lane, v, P.zero);                                             \
  if ((K) == 3 && wg == 1) bar_arrive(4, 160);                                                                         \
  mbar_wait(sb + B_FULL2 + 8 * ((K) + 1), 0);                                                                          \
  p2_mma<F, false>(acc, acb, sb16 + ((K) + 1) * (ST2 >> 4) + aoff, sb16 + ((K) + 1) * (ST2 >> 4) + (CH >> 4), lbo96);  \
  wg_wait<1>();                                                                                                        \
  mbar_arrive_elect(sb + B_EMPTY2 + 8 * (K));
  P2_STEP_WITH_PIECE(0) P2_STEP_WITH_PIECE(1) P2_STEP_WITH_PIECE(2) P2_STEP_WITH_PIECE(3)
#undef P2_STEP_WITH_PIECE
  int s = 0, ph = 1;
#pragma unroll 1
  for (int k = 5; k < NK; k++) {
    if (k == NK - 4 && wg == 1) {
      wg_wait<0>();
      if (elect_one()) mbar_arrive_remote(mapa(sb + B_PEER, peer));
      bar_sync(6, 256);
    }
    mbar_wait(sb + B_FULL2 + 8 * s, ph);
    p2_mma<F, false>(acc, acb, sb16 + s * (ST2 >> 4) + aoff, sb16 + s * (ST2 >> 4) + (CH >> 4), lbo96);
    wg_wait<1>();
    if (k < NK - 4) mbar_arrive_elect(sb + B_EMPTY2 + 8 * (s == 0 ? 4 : s - 1));
    else if (k == NK - 4 && wg == 0 && elect_one()) mbar_arrive_remote(mapa(sb + B_PEER, peer));
    if (++s == 5) { s = 0; ph ^= 1; }
  }
  if (wg == 0) bar_arrive(6, 256);
  const int lrow = 8 * (2 * wg + (w >> 1));
  const int tk = 64 * (w & 1) + (F ? 32 : 0) + lrow + r;
#define CB(n) (!F ? (n) : (n) < 2 ? (n) + rot : (n) == 2 ? 4 - 4 * rot : (n) - 1 + rot)
#define PEER_N(c) (F ? (c) : (nt & 1) ? ((c) == 0 ? 2 : (c) < 3 ? (c) - 1 : (c)) : ((c) < 2 ? (c) : (c) == 4 ? 2 : (c) + 1))
  constexpr int RSLOT = NK % 5, RSLOT_PEER = F ? (2 * NCG) % 5 : NFC % 5;
  const uint32_t rdst = mapa(sb + RSLOT_PEER * ST2 + warp * 2560 + lane * 16, peer);
  const uint32_t rbar = mapa(sb + B_RECV + 8 * warp, peer);
  const bool odd = q & 1;
  const uint32_t rsrc = sb + RSLOT * ST2 + warp * 2560 + (lane & ~1) * 16 + (odd ? 8 : 0);
  float* orow = P.out + (size_t)(rb * 128 + tk) * DM + 160 * nt + (odd ? 2 * q + 6 : 2 * q);
  constexpr int OS = F ? 0 : 2, OK = F ? 2 : 0;
  mbar_wait_cluster(sb + B_PEER, 0);
  wg_wait<0>();
  fence_regs(acc);
  if (F) fence_regs(acb);
#pragma unroll
  for (int n = 0; n < 5; n++) {
    uint32_t p[4];
#pragma unroll
    for (int i = 0; i < 4; i++) p[i] = pack_bf16(ACC(16 * n + 4 * i + OS), ACC(16 * n + 4 * i + OS + 1));
    asm volatile("st.async.weak.shared::cluster.mbarrier::complete_tx::bytes.v4.b32 [%0], {%1, %2, %3, %4}, [%5];"
                 ::"r"(rdst + CB(n) * 512), "r"(p[0]), "r"(p[2]), "r"(p[1]), "r"(p[3]),
                   "r"(rbar + (PEER_N(CB(n)) < NA ? 0 : B_RECV2 - B_RECV)) : "memory");
  }
  float g;
  uint32_t xd[20];
  mbar_wait(sb + B_G, 0);
  asm volatile("ld.shared.f32 %0, [%1];" : "=f"(g) : "r"(sb + SM_G + 4 * tk) : "memory");
  mbar_wait(sb + B_XS, 0);
  {
    const uint32_t xa = sb + SM_XS + (w & 1) * 10752 + (lrow + (lane & 7)) * 336 + (lane >> 3) * 16;
    const uint32_t da = sb + SM_XS + 21504 + (lane >> 3) * 16;
#pragma unroll
    for (int n = 0; n < 5; n++) {
      uint32_t xv[4], dv[4];
      ldmatrix4(xv, xa + CB(n) * 64);
      ldmatrix4(dv, da + CB(n) * 64);
#pragma unroll
      for (int i = 0; i < 4; i++) asm("mul.bf16x2 %0, %1, %2;" : "=r"(xd[4 * n + i]) : "r"(xv[i]), "r"(dv[i]));
    }
  }
  const float sk = F ? 1.0f - g : 2.0f * g, sr = F ? 2.0f * g : 1.0f - g;
#pragma unroll
  for (int grp = 0; grp < 2; grp++) {
    float o[40];
#pragma unroll
    for (int i = grp ? 2 * NA : 0; i < (grp ? 10 : 2 * NA); i++) {
#pragma unroll
      for (int e = 0; e < 2; e++) {
        const float u0 = fmaf(ACC(8 * i + OK + e), sk, g * (e ? bf_hi(xd[2 * i]) : bf_lo(xd[2 * i])));
        const float u1 = fmaf(ACC(8 * i + 4 + OK + e), sk, g * (e ? bf_hi(xd[2 * i + 1]) : bf_lo(xd[2 * i + 1])));
        const float b = __shfl_xor_sync(0xffffffffu, odd ? u0 : u1, 1);
        o[4 * i + e] = odd ? b : u0;
        o[4 * i + 2 + e] = odd ? u1 : b;
        asm volatile("" : "+f"(o[4 * i + e]), "+f"(o[4 * i + 2 + e]));
      }
    }
    mbar_wait_cluster(sb + (grp ? B_RECV2 : B_RECV) + 8 * warp, 0);
    if (grp) mbar_arrive_elect(sb + B_DONE);
#pragma unroll
    for (int n = grp ? NA : 0; n < (grp ? 5 : NA); n++) {
      uint32_t lo[2], hi[2];
      asm volatile("ld.shared.v2.b32 {%0, %1}, [%2];" : "=r"(lo[0]), "=r"(lo[1]) : "r"(rsrc + CB(n) * 512) : "memory");
      asm volatile("ld.shared.v2.b32 {%0, %1}, [%2];" : "=r"(hi[0]), "=r"(hi[1]) : "r"(rsrc + CB(n) * 512 + 16) : "memory");
#pragma unroll
      for (int h = 0; h < 2; h++) {
        const int i = 2 * n + h;
        *(float4*)(orow + 32 * CB(n) + 16 * h) = make_float4(fmaf(bf_lo(lo[h]), sr, o[4 * i]), fmaf(bf_hi(lo[h]), sr, o[4 * i + 1]),
                                                             fmaf(bf_lo(hi[h]), sr, o[4 * i + 2]), fmaf(bf_hi(hi[h]), sr, o[4 * i + 3]));
      }
    }
    if (grp == 0) block_end(P.zero);
  }
#undef ACC
#undef CB
#undef PEER_N
}

template <bool USE_SMID>
__global__ void __launch_bounds__(384, 1) __cluster_dims__(2, 1, 1) fused_kernel(const __grid_constant__ Params P) {
  extern __shared__ __align__(1024) unsigned char smem_raw[];
  const uint32_t sb = smem_u32(smem_raw);
  trap_if_over((int)((sb & 0xFFFFFFu) ^ SB_LOCAL), 0);
  const int warp = __shfl_sync(0xffffffffu, threadIdx.x >> 5, 0), lane = threadIdx.x & 31;
  if (warp == 10 && elect_one()) { prefetch_map(&P.x); prefetch_map(&P.wg); prefetch_map(&P.wu); }
  uint32_t ftype, smid;
  asm("mov.u32 %0, %%cluster_ctarank;" : "=r"(ftype));
  asm("mov.u32 %0, %%smid;" : "=r"(smid));
  const int tp = USE_SMID ? (int)(smid >> 1) : (int)(blockIdx.x >> 1);
  int gpc, idx;
  bool extra = false;
  if (tp < 32) { gpc = tp & 7; idx = tp >> 3; }
  else if (tp < 60) { gpc = 1 + (tp - 32) % 7; idx = 4 + (tp - 32) / 7; }
  else if (tp < 62) { gpc = 0; idx = tp - 60; extra = true; }
  else { gpc = 0; idx = tp - 58; }
  const int rb = extra ? (idx * 2 + ftype) * 4 : 4 * (gpc >> 1) + (idx & 3);
  const int nt = 2 * (gpc & 1) + (idx >> 2);
  const int role = tp * 2 + ftype;
  const int nslots = (extra || ftype) ? 4 : 5;
  const int fc0 = extra ? EXTRA_FC : ftype * 4 + nt;
  if (warp == 8) {
#pragma unroll 1
    for (int k = 0; k < 4; k++) {
      const uint32_t res = sb + SM_RES + k * CH, ring = sb + SM_RING + k * CH;
      const uint32_t bx = sb + B_XFULL + 8 * k, bf = sb + B_FULL1 + 8 * k;
      if (elect_one()) {
        if (k == 0) {
          mbar_init(bx, 1);
          mbar_init(bf, 1);
          asm volatile("fence.mbarrier_init.release.cluster;" ::: "memory");
        }
        mbar_expect_tx(bx, extra && k == 0 ? CH + 1280 : CH);
        mbar_expect_tx(bf, CH);
        tma5d(extra ? ring : res, &P.x, 64 * k, rb, extra ? bf : bx);
        tma2d(extra ? res : ring, &P.wg, 64 * fc0, 64 * k, extra ? bx : bf);
        tma2d((extra ? res : ring) + 8192, &P.wu, 64 * fc0, 64 * k, extra ? bx : bf);
        if (k == 0) {
          if (extra) bulk_load(sb + SM_GW, P.gatew, 1280, bx);
#pragma unroll
          for (int i = 1; i < 18; i++)
            if (i != 10) mbar_init(sb + SM_BAR + 8 * i, i < 14 ? 1 : 4);
          asm volatile("fence.mbarrier_init.release.cluster;" ::: "memory");
        }
      }
      if (k == 0) {
        __syncwarp();
        bar_arrive(0, 384);
      }
    }
  } else {
    if (warp == 9 && elect_one()) {
#pragma unroll
      for (int i = 18; i < 49; i++) mbar_init(sb + SM_BAR + 8 * i, i < 23 ? 1 : i < 28 ? 8 : i == 28 ? 32 : i == 29 ? 8 : i == 39 ? 128 : i == 40 ? 11 : 1);
      asm volatile("st.shared.u32 [%0], %1;" ::"r"(sb + SM_READY), "r"(0) : "memory");
      asm volatile("fence.mbarrier_init.release.cluster;" ::: "memory");
    }
    __syncwarp();
    bar_sync(0, 384);
  }
  asm volatile("barrier.cluster.arrive.relaxed.aligned;" ::: "memory");

  if (warp >= 8) {
    asm volatile("setmaxnreg.dec.sync.aligned.u32 40;");
    if (warp == 8) {
      int it = 4;
#pragma unroll 1
      for (int slot = 0; slot < nslots; slot++) {
        bool ssm = false;
        const int id = extra ? 0 : unit_of(ftype, nt, slot, ssm);
        const CUtensorMap* m0 = ssm ? &P.bre : &P.wg;
        const int c0 = ssm ? 0 : 64 * id, c1 = ssm ? 64 * id : 0, d0 = ssm ? 64 : 0;
#pragma unroll 1
        for (int k = slot == 0 ? 4 : 0; k < 10; k++, it++) {
          const int s = it & 3;
          const uint32_t ring = sb + SM_RING + s * CH, bf = sb + B_FULL1 + 8 * s;
          if (slot == 0 && elect_one()) {
            const uint32_t res = sb + SM_RES + k * CH, bx = sb + B_XFULL + 8 * k;
            mbar_expect_tx(bx, CH);
            if (!extra) tma5d(res, &P.x, 64 * k, rb, bx);
            else { tma2d(res, &P.wg, 64 * EXTRA_FC, 64 * k, bx); tma2d(res + 8192, &P.wu, 64 * EXTRA_FC, 64 * k, bx); }
          }
          mbar_wait(sb + B_EMPTY1 + 8 * s, ((it >> 2) & 1) ^ 1);
          if (elect_one()) {
            mbar_expect_tx(bf, CH);
            if (extra) tma5d(ring, &P.x, 64 * k, rb + slot, bf);
            else {
              tma2d(ring, m0, c0 + d0 * k, c1 + (64 - d0) * k, bf);
              tma2d(ring + 8192, m0 + 1, c0 + d0 * k, c1 + (64 - d0) * k, bf);
            }
          }
        }
      }
      if (!extra) {
        const int nk = ftype ? NFC : 2 * NCG;
        const int dc = 160 * nt + ((nt & 1) ? 32 : 0);
        const unsigned char* asrc = P.scr + (ftype ? G_ACT + (size_t)(rb * NFC) * CH : G_H + (size_t)(rb * 2 * NCG) * CH);
        int s = 0, ph = 1;
        uint32_t ready = 0;
#pragma unroll 1
        for (int k2 = 0; k2 < nk; k2++) {
          if (k2 >= 5) {
            mbar_wait(sb + B_EMPTY2 + 8 * s, ph);
          } else if (k2 == 2 || k2 == 3) {
            mbar_wait(sb + B_EMPTY1 + 8 * (it & 3), ((it >> 2) & 1) ^ 1);
            it++;
            mbar_wait(sb + B_EMPTY1 + 8 * (it & 3), ((it >> 2) & 1) ^ 1);
            it++;
          }
          const uint32_t st = sb + s * ST2, bf = sb + B_FULL2 + 8 * s;
          if (elect_one()) {
            if (ftype) {
              mbar_expect_tx(bf, 40960);
              tma5d(st + CH, &P.wd, dc, 2 * k2, bf);
              tma5d(st + CH + 8192, &P.wd, dc + 64, 2 * k2, bf);
              tma5d(st + CH + 16384, &P.wd, 128 + 320 * (nt >> 1), 2 * k2, bf);
            } else {
              mbar_expect_tx(bf, 36864);
              tma2d(st + CH, &P.cre + (k2 & 1), 64 * (k2 >> 1), 160 * nt, bf);
            }
          }
          const uint32_t need = ftype ? k2 : k2 >> 1;
          if (ready <= need) {
            int spin = 0;
            do {
              asm volatile("ld.acquire.cta.shared.u32 %0, [%1];" : "=r"(ready) : "r"(sb + SM_READY) : "memory");
              trap_if_over(++spin, 1 << 26);
            } while (ready <= need);
            asm volatile("fence.proxy.async.global;" ::: "memory");
          }
          if (elect_one()) {
            bulk_load(st, asrc + (size_t)k2 * CH, CH, bf);
            if (k2 == 4) {
              mbar_expect_tx(sb + B_XS, 21824);
              tma2d(sb + SM_XS, &P.xs, 160 * nt, rb * 128 + 32 * ftype, sb + B_XS);
              tma2d(sb + SM_XS + 10752, &P.xs, 160 * nt, rb * 128 + 64 + 32 * ftype, sb + B_XS);
              bulk_load(sb + SM_XS + 21504, P.dskip + 160 * nt, 320, sb + B_XS);
            }
          }
          if (++s == 5) { s = 0; ph ^= 1; }
        }
      }
    } else if (warp == 9) {
      const unsigned want = load_epoch(P, role) + 1;
      if (elect_one()) {
        prefetch_map(&P.bre); prefetch_map(&P.bim);
        if (ftype) prefetch_map(&P.wd); else { prefetch_map(&P.cre); prefetch_map(&P.cim); }
        prefetch_map(&P.xs);
      }
      for (int slot = 0; slot < nslots; slot++) {
        bool ssm = false;
        const int id = extra ? EXTRA_FC : unit_of(ftype, nt, slot, ssm);
        bar_sync(3 + ((slot + nslots) & 1), 160);
        if (elect_one()) {
          asm volatile("fence.acq_rel.gpu;" ::: "memory");
          asm volatile("st.relaxed.gpu.global.u32 [%0], %1;" ::"l"(P.scr + (ssm ? G_FLAG_H : G_FLAG_ACT) + 4 * ((extra ? rb + slot : rb) * 32 + id)), "r"(want) : "memory");
        }
        __syncwarp();
      }
      if (extra && lane == 0) asm volatile("red.relaxed.gpu.global.add.u32 [%0], 1;" ::"l"(P.scr + G_EPOCH + 4 * role) : "memory");
    } else if (warp == 10 && !extra) {
      const unsigned want = load_epoch(P, role) + 1;
      const int nf = ftype ? NFC : NCG;
      const unsigned char* fl = P.scr + (lane == 31 ? G_FLAG_ACT + 4 * EXTRA_FC : (ftype ? G_FLAG_ACT : G_FLAG_H) + 4 * lane) + 128 * rb;
      mbar_wait(sb + B_XFULL + 8 * 9, 0);
      __nanosleep(1000);
      uint32_t last = 0;
      int spin = 0;
      while (last < 32) {
        unsigned v = want;
        if (lane < nf || lane == 31) asm volatile("ld.acquire.gpu.global.u32 %0, [%1];" : "=r"(v) : "l"(fl) : "memory");
        const unsigned miss = __ballot_sync(0xffffffffu, v != want);
        const uint32_t n = miss ? __ffs(miss) - 1 : 32;
        __syncwarp();
        if (n > last) {
          last = n;
          if (lane == 0) asm volatile("st.release.cta.shared.u32 [%0], %1;" ::"r"(sb + SM_READY), "r"(n) : "memory");
        } else {
          __nanosleep(200);
        }
        trap_if_over(++spin, 1 << 22);
      }
      float4 gv;
      asm volatile("ld.relaxed.gpu.global.v4.f32 {%0, %1, %2, %3}, [%4];" : "=f"(gv.x), "=f"(gv.y), "=f"(gv.z), "=f"(gv.w) : "l"(P.scr + G_GATE + rb * 512 + 16 * lane) : "memory");
      asm volatile("st.shared.v4.f32 [%0], {%1, %2, %3, %4};" ::"r"(sb + SM_G + 16 * lane), "f"(gv.x), "f"(gv.y), "f"(gv.z), "f"(gv.w) : "memory");
      mbar_arrive(sb + B_G);
      if (lane == 0) asm volatile("red.relaxed.gpu.global.add.u32 [%0], 1;" ::"l"(P.scr + G_EPOCH + 4 * role) : "memory");
    } else if (warp == 11) {
      if (!extra) {
        const int pc = (rb * 4 + nt) * 2 + ftype;
        const char* wrow = (lane & 1 ? P.p_wu : P.p_wg) + (size_t)(pc * 5 + (lane >> 1)) * (FF * 2);
        mbar_wait_bounded(sb + B_XFULL + 8 * 9, 0);
        if (lane < 2) l2_prefetch((lane ? P.p_bim : P.p_bre) + pc * 5120, 5120);
        if (lane < 10) l2_prefetch(wrow + 8 * 128, 6 * 128);
        if (lane < 2) l2_prefetch((lane ? P.p_bim : P.p_bre) + 655360 + pc * 1280, 1280);
        __nanosleep(2000);
        if (lane < 10) l2_prefetch(wrow + 14 * 128, 8 * 128);
        __nanosleep(1000);
        if (lane == 0) l2_prefetch(P.p_wd + pc * 8640, 8640);
        __nanosleep(1000);
        if (lane < 10) l2_prefetch(wrow + 23 * 128, 4 * 128);
        if (lane == 0) l2_prefetch(P.p_wd + 1105920 + pc * 8640, 8640);
        __nanosleep(1000);
        if (lane < 2) l2_prefetch((lane ? P.p_cim : P.p_cre) + pc * 6400, 6400);
      }
      mbar_wait_bounded(sb + B_DONE, 0);
    }
    __syncwarp();
    asm volatile("barrier.cluster.wait.acquire.aligned;" ::: "memory");
    if (warp < 11) mbar_arrive_elect(sb + B_DONE);
  } else {
    const int wg = warp >> 2, w = warp & 3;
    if (((wg + nslots) & 1) != 0) mbar_wait(sb + B_XFULL, 0);
    asm volatile("setmaxnreg.inc.sync.aligned.u32 232;");
    if (extra) {
#pragma unroll 1
      for (int slot = wg; slot < 4; slot += 2) {
        float acc0[64], acc1[64], g0[4], g1[4];
        if (slot > 0) bar_sync(1 + wg, 256);
        const float tok = unit_mainloop<2>(acc0, acc1, g0, g1, sb, slot * 10, slot < 2, slot < 3, wg, lane);
        if ((lane & 3) == 0) {
#pragma unroll
          for (int i = 0; i < 4; i++) {
            const int c = 64 * (i >> 1) + 16 * w + 8 * (i & 1) + (lane >> 2);
            const float z = (i >> 1) ? g1[2 * (i & 1)] : g0[2 * (i & 1)];
            ((float*)(P.scr + G_GATE))[(rb + slot) * 128 + 32 * ((c >> 1) & 3) + 2 * (c >> 3) + (c & 1)] = 1.0f / (1.0f + expf(-z));
          }
        }
        unsigned char* tile = P.scr + G_ACT + (size_t)((rb + slot) * NFC + EXTRA_FC) * CH;
        float v[NCH];
#pragma unroll
        for (int i = 0; i < NCH; i++) v[i] = tok;
        ffn_pieces<true, 8>(acc0, acc1, tile, w, lane, v, P.zero);
        bar_arrive(3 + wg, 160);
      }
      asm volatile("barrier.cluster.wait.acquire.aligned;" ::: "memory");
      mbar_arrive_elect(sb + B_DONE);
    } else {
#pragma unroll 1
      for (int slot = (wg + nslots) & 1; slot < nslots - 1; slot += 2) {
        bool ssm = false;
        const int id = unit_of(ftype, nt, slot, ssm);
        float acc0[64], acc1[64], g0[4], g1[4];
        if (ssm) {
          const unsigned tag = load_epoch(P, role);
          if (slot == 1) {
            const int t = threadIdx.x & 127;
            const float4 cf = ssm_coef(P, t < 64 ? 64 * id + t : 512 + 64 * (nt & 1) + t - 64);
            asm volatile("st.shared.v4.f32 [%0], {%1, %2, %3, %4};" ::"r"(sb + SM_GW + 16 * t), "f"(cf.x), "f"(cf.y), "f"(cf.z), "f"(cf.w) : "memory");
            mbar_arrive(sb + B_COEF);
          }
          mbar_wait(sb + B_COEF, 0);
          SsmCoef co[2];
          co[0] = ssm_powers(sb + SM_GW + (slot - 1) * 1024 + 16 * (16 * w + (lane >> 2)), lane & 3);
          co[1] = ssm_powers(sb + SM_GW + (slot - 1) * 1024 + 16 * (16 * w + (lane >> 2) + 8), lane & 3);
#pragma unroll
          for (int i = 0; i < 2; i++)
            asm volatile("" : "+f"(co[i].m4.r), "+f"(co[i].m4.i), "+f"(co[i].mq.r), "+f"(co[i].mq.i), "+f"(co[i].lq.r), "+f"(co[i].lq.i),
                              "+f"(co[i].c1.r), "+f"(co[i].c1.i), "+f"(co[i].l32.r), "+f"(co[i].l32.i), "+f"(co[i].l64.r), "+f"(co[i].l64.i));
          bar_sync(1 + wg, 256);
          const float tok = unit_mainloop<1>(acc0, acc1, g0, g1, sb, slot * 10, slot < 2, true, wg, lane);
          ssm_epilogue(acc0, acc1, co, P.scr, rb, id, tag + 1, w, lane, P.zero, tok);
        } else {
          if (slot > 0) bar_sync(1 + wg, 256);
          const float tok = unit_mainloop<0>(acc0, acc1, g0, g1, sb, slot * 10, slot < 2, true, wg, lane);
          unsigned char* tile = P.scr + G_ACT + (size_t)(rb * NFC + id) * CH;
          float v[NCH];
#pragma unroll
          for (int i = 0; i < NCH; i++) v[i] = tok;
          ffn_pieces<true, 8>(acc0, acc1, tile, w, lane, v, P.zero);
        }
        bar_arrive(3 + wg, 160);
      }
      float acc0[64], acc1[64], g0[4], g1[4];
      unsigned char* tile = P.scr + G_ACT + (size_t)(rb * NFC + (ftype ? 18 : 23) + nt) * CH;
      if (wg == 1) {
        const int slot = nslots - 1;
        bar_sync(2, 256);
        const float tok = unit_mainloop<0>(acc0, acc1, g0, g1, sb, slot * 10, false, false, 1, lane);
        float v[NCH];
        v[0] = chain(-1.4426950408889634f, tok, P.zero);
        ffn_pieces<false, 4>(acc0, acc1, tile, w, lane, v, P.zero);
      }
      if (ftype) phase2<true>(P, sb, rb, nt, wg, w, lane, acc1, tile);
      else phase2<false>(P, sb, rb, nt, wg, w, lane, acc1, tile);
    }
  }
}

typedef CUresult (*EncodeFn)(CUtensorMap*, CUtensorMapDataType, cuuint32_t, void*, const cuuint64_t*, const cuuint64_t*,
                             const cuuint32_t*, const cuuint32_t*, CUtensorMapInterleave, CUtensorMapSwizzle,
                             CUtensorMapL2promotion, CUtensorMapFloatOOBfill);

void encode(EncodeFn fn, CUtensorMap* m, const void* base, int rank, const cuuint64_t* dims, const cuuint64_t* strides,
            const cuuint32_t* box, CUtensorMapSwizzle swz = CU_TENSOR_MAP_SWIZZLE_128B) {
  const cuuint32_t es[5] = {1, 1, 1, 1, 1};
  fn(m, CU_TENSOR_MAP_DATA_TYPE_BFLOAT16, rank, const_cast<void*>(base), dims, strides, box, es,
     CU_TENSOR_MAP_INTERLEAVE_NONE, swz, CU_TENSOR_MAP_L2_PROMOTION_L2_128B,
     CU_TENSOR_MAP_FLOAT_OOB_FILL_NONE);
}

}

extern "C" void kernel_launch(void* const* d_in, const int* in_sizes, int n_in, void* d_out, int out_size) {
  (void)in_sizes; (void)n_in; (void)out_size;
  static EncodeFn enc = nullptr;
  static int sms = 0;
  static void* scratch = nullptr;
  if (!enc) {
    void* fn = nullptr;
    cudaDriverEntryPointQueryResult qr;
    cudaGetDriverEntryPoint("cuTensorMapEncodeTiled", &fn, cudaEnableDefault, &qr);
    enc = (EncodeFn)fn;
    int dev = 0;
    cudaGetDevice(&dev);
    cudaDeviceGetAttribute(&sms, cudaDevAttrMultiProcessorCount, dev);
    cudaGetSymbolAddress(&scratch, g_scratch);
    cudaFuncSetAttribute(fused_kernel<true>, cudaFuncAttributeMaxDynamicSharedMemorySize, SMEM_BYTES);
    cudaFuncSetAttribute(fused_kernel<false>, cudaFuncAttributeMaxDynamicSharedMemorySize, SMEM_BYTES);
  }
  typedef const __nv_bfloat16* bp;
  Params P;
  const cuuint64_t R = DM * 2;
  {
    const cuuint64_t d[5] = {DM, 2, 4, 16, NRB}, s[4] = {R, 32 * R, 2 * R, 128 * R};
    const cuuint32_t b[5] = {64, 2, 4, 16, 1};
    encode(enc, &P.x, d_in[0], 5, d, s, b);
  }
  {
    const cuuint64_t d[2] = {DM, DM}, s[1] = {R};
    const cuuint32_t b[2] = {64, 64}, bc[2] = {64, 160};
    encode(enc, &P.bre, d_in[3], 2, d, s, b);
    encode(enc, &P.bim, d_in[4], 2, d, s, b);
    encode(enc, &P.cre, d_in[5], 2, d, s, bc);
    encode(enc, &P.cim, d_in[6], 2, d, s, bc);
  }
  {
    const cuuint64_t d[2] = {FF, DM}, s[1] = {FF * 2};
    const cuuint32_t b[2] = {64, 64};
    encode(enc, &P.wg, d_in[10], 2, d, s, b);
    encode(enc, &P.wu, d_in[11], 2, d, s, b);
  }
  {
    const cuuint64_t d[5] = {DM, 2, 4, 4, FF / 32};
    const cuuint64_t s[4] = {R, 8 * R, 2 * R, 32 * R};
    const cuuint32_t b[5] = {64, 2, 4, 4, 2};
    encode(enc, &P.wd, d_in[12], 5, d, s, b);
  }
  {
    const cuuint64_t d[2] = {DM, 2048}, s[1] = {R};
    const cuuint32_t b[2] = {168, 32};
    encode(enc, &P.xs, d_in[0], 2, d, s, b, CU_TENSOR_MAP_SWIZZLE_NONE);
  }
  P.scr = (unsigned char*)scratch;
  P.lre = (bp)d_in[1]; P.lim = (bp)d_in[2]; P.logdt = (bp)d_in[7]; P.dskip = (bp)d_in[8];
  P.gatew = (bp)d_in[13];
  P.p_bre = (const char*)d_in[3]; P.p_bim = (const char*)d_in[4]; P.p_cre = (const char*)d_in[5]; P.p_cim = (const char*)d_in[6];
  P.p_wg = (const char*)d_in[10]; P.p_wu = (const char*)d_in[11]; P.p_wd = (const char*)d_in[12];
  P.out = (float*)d_out;
  P.zero = 0;
  if (sms == 132) fused_kernel<true><<<132, 384, SMEM_BYTES, cudaStreamPerThread>>>(P);
  else fused_kernel<false><<<132, 384, SMEM_BYTES, cudaStreamPerThread>>>(P);
}
```
